```python
import torch

def _softmax(x, axis=-1):
    return torch.softmax(x, dim=axis)

def _gelu(x):
    return torch.nn.functional.gelu(x, approximate='tanh')

def _silu(x):
    return torch.nn.functional.silu(x)

def _sigmoid(x):
    return torch.sigmoid(x)

def _layernorm(x, axis=-1, eps=1e-05):
    m = x.mean(dim=axis, keepdim=True)
    v = x.var(dim=axis, keepdim=True, unbiased=False)
    return (x - m) / torch.sqrt(v + eps)

def _scatter_add(tgt, idx, src, axis=0):
    return tgt.clone().index_add_(axis, idx, src)

def _segment_sum(src, seg, n):
    out = torch.zeros((n,) + src.shape[1:], dtype=src.dtype)
    return out.index_add_(0, seg, src)

def _pad(x, pw):
    flat = tuple((v for pair in reversed(pw) for v in pair))
    return torch.nn.functional.pad(x, flat)
kernel_name = 'gated_mix__memory_aug_recurrent_mem_tr__glu_gated_glu__prompt'

def setup_inputs():

    _w = lambda a: (lambda t: t.to(torch.bfloat16) if t.is_floating_point() else t)(torch.as_tensor(a))

    def _A_setup():
        B, S, Dm = (1, 2048, 640)
        H, Dh = (32, 192)
        M, seg = (8, 32)
        seg = min(seg, S)
        S = S // seg * seg
        return {'x': _w((lambda *s: torch.randn(*s, dtype=torch.bfloat16) * 0.05)(B, S, Dm)), 'mem0': _w((lambda *s: torch.randn(*s, dtype=torch.bfloat16) * 0.8)(B, M, Dm)), 'Wq': _w((lambda *s: torch.randn(*s, dtype=torch.bfloat16) * 1.6)(Dm, H, Dh) * Dm ** (-0.5)), 'Wk': _w((lambda *s: torch.randn(*s, dtype=torch.bfloat16) * 1.6)(Dm, H, Dh) * Dm ** (-0.5)), 'Wv': _w((lambda *s: torch.randn(*s, dtype=torch.bfloat16) * 0.8)(Dm, H, Dh) * Dm ** (-0.5)), 'Wo': _w((lambda *s: torch.randn(*s, dtype=torch.bfloat16) * 0.8)(H, Dh, Dm) * (H * Dh) ** (-0.5)), 'seg_len': seg}
    _A_in = _A_setup()

    def _B_setup():
        B, S, D, F = (1, 2048, 640, 1536)
        return {'x': _w((lambda *s: torch.randn(*s, dtype=torch.bfloat16) * 0.05)(B, S, D)), 'w_gate': _w((lambda *s: torch.randn(*s, dtype=torch.bfloat16) * 0.4)(D, F)), 'w_up': _w((lambda *s: torch.randn(*s, dtype=torch.bfloat16) * 0.05)(D, F)), 'w_down': _w((lambda *s: torch.randn(*s, dtype=torch.bfloat16) * 0.05)(F, D))}
    _B_in = _B_setup()
    return {'A_x': _A_in['x'], 'A_mem0': _A_in['mem0'], 'A_Wq': _A_in['Wq'], 'A_Wk': _A_in['Wk'], 'A_Wv': _A_in['Wv'], 'A_Wo': _A_in['Wo'], 'A_seg_len': _A_in['seg_len'], 'B_x': _B_in['x'], 'B_w_gate': _B_in['w_gate'], 'B_w_up': _B_in['w_up'], 'B_w_down': _B_in['w_down'], 'gate_w': _w((lambda *s: torch.randn(*s, dtype=torch.bfloat16) * 0.05)(640) * 16.0)}

def reference(A_x, A_mem0, A_Wq, A_Wk, A_Wv, A_Wo, A_seg_len, B_x, B_w_gate, B_w_up, B_w_down, gate_w):

    def _A_ref(x, mem0, Wq, Wk, Wv, Wo, seg_len):
        B, S, Dm = x.shape
        H, Dh = (Wq.shape[1], Wq.shape[2])
        M = mem0.shape[1]
        scale = Dh ** (-0.5)
        n_seg = S // seg_len
        L = M + seg_len
        idx = torch.arange(L)
        mask = (idx[:, None] < M) | (idx[:, None] >= idx[None, :])
        mem = mem0
        outs = []
        for s in range(n_seg):
            xs = x[:, s * seg_len:(s + 1) * seg_len, :].clone()
            h = torch.concatenate([mem, xs], axis=1)
            q = torch.einsum('btd,dhe->bhte', h, Wq)
            k = torch.einsum('btd,dhe->bhte', h, Wk)
            v = torch.einsum('btd,dhe->bhte', h, Wv)
            scores = torch.einsum('bhqe,bhke->bhqk', q, k) * scale
            scores = torch.where(mask[None, None], scores, -1000000000.0)
            p = _softmax(scores, axis=-1)
            o = torch.einsum('bhqk,bhke->bhqe', p, v)
            o = torch.einsum('bhte,hed->btd', o, Wo)
            mem = o[:, :M, :].clone()
            outs.append(o[:, M:, :])
        return torch.concatenate(outs, axis=1)

    def _B_ref(x, w_gate, w_up, w_down):
        g = torch.einsum('bsd,df->bsf', x, w_gate)
        u = torch.einsum('bsd,df->bsf', x, w_up)
        h = _sigmoid(g) * u
        return torch.einsum('bsf,fd->bsd', h, w_down)
    x = A_x
    g = _sigmoid((x * gate_w).sum(-1, keepdims=True))
    a = _A_ref(x, A_mem0, A_Wq, A_Wk, A_Wv, A_Wo, A_seg_len)
    b = _B_ref(x, B_w_gate, B_w_up, B_w_down)
    return g * a + (1 - g) * b
```

```cpp
#include <cuda_runtime.h>
#include <cuda_bf16.h>
#include <cuda.h>
#include <stdint.h>
#include <type_traits>

typedef __nv_bfloat16 bf16;

#define DEVINL __device__ __forceinline__

DEVINL uint32_t smem_u32(const void* p) { return (uint32_t)__cvta_generic_to_shared(p); }

DEVINL void mbar_init(uint32_t bar, uint32_t count) {
    asm volatile("mbarrier.init.shared::cta.b64 [%0], %1;" ::"r"(bar), "r"(count) : "memory");
}
DEVINL void mbar_expect_tx(uint32_t bar, uint32_t bytes) {
    asm volatile("mbarrier.arrive.expect_tx.shared::cta.b64 _, [%0], %1;" ::"r"(bar), "r"(bytes) : "memory");
}
DEVINL void mbar_arrive(uint32_t bar) {
    asm volatile("mbarrier.arrive.shared::cta.b64 _, [%0];" ::"r"(bar) : "memory");
}
#define SPIN_LIMIT (1u << 22)
DEVINL void mbar_wait(uint32_t bar, uint32_t parity) {
    asm volatile(
        "{\n.reg .pred p, q;\n.reg .u32 n;\nmov.u32 n, 0;\n"
        "WAIT_LOOP:\n"
        "mbarrier.try_wait.parity.shared::cta.b64 p, [%0], %1;\n"
        "@p bra WAIT_DONE;\n"
        "add.u32 n, n, 1;\n"
        "setp.lt.u32 q, n, 4194304;\n"
        "@q bra WAIT_LOOP;\n"
        "trap;\n"
        "WAIT_DONE:\n}\n" ::"r"(bar), "r"(parity) : "memory");
}
DEVINL void fence_proxy_async() { asm volatile("fence.proxy.async.shared::cta;" ::: "memory"); }
DEVINL void bar_sync(int id, int n) { asm volatile("bar.sync %0, %1;" ::"r"(id), "r"(n) : "memory"); }
DEVINL void bar_arrive(int id, int n) { asm volatile("bar.arrive %0, %1;" ::"r"(id), "r"(n) : "memory"); }

DEVINL void tma_load_2d(uint32_t dst, const CUtensorMap* map, int c0, int c1, uint32_t bar) {
    asm volatile(
        "cp.async.bulk.tensor.2d.shared::cluster.global.mbarrier::complete_tx::bytes [%0], [%1, {%3, %4}], [%2];"
        ::"r"(dst), "l"(map), "r"(bar), "r"(c0), "r"(c1) : "memory");
}
DEVINL void tma_prefetch_2d(const CUtensorMap* map, int c0, int c1) {
    asm volatile("cp.async.bulk.prefetch.tensor.2d.L2.global [%0, {%1, %2}];" ::"l"(map), "r"(c0), "r"(c1) : "memory");
}

DEVINL void ldsm_x4(uint32_t& r0, uint32_t& r1, uint32_t& r2, uint32_t& r3, uint32_t addr) {
    asm volatile("ldmatrix.sync.aligned.m8n8.x4.shared.b16 {%0,%1,%2,%3}, [%4];"
                 : "=r"(r0), "=r"(r1), "=r"(r2), "=r"(r3) : "r"(addr) : "memory");
}
DEVINL void ldsm_x4_t(uint32_t& r0, uint32_t& r1, uint32_t& r2, uint32_t& r3, uint32_t addr) {
    asm volatile("ldmatrix.sync.aligned.m8n8.x4.trans.shared.b16 {%0,%1,%2,%3}, [%4];"
                 : "=r"(r0), "=r"(r1), "=r"(r2), "=r"(r3) : "r"(addr) : "memory");
}
DEVINL void ldsm_x2_t(uint32_t& r0, uint32_t& r1, uint32_t addr) {
    asm volatile("ldmatrix.sync.aligned.m8n8.x2.trans.shared.b16 {%0,%1}, [%2];"
                 : "=r"(r0), "=r"(r1) : "r"(addr) : "memory");
}
DEVINL void stsm_x2_t(uint32_t addr, uint32_t r0, uint32_t r1) {
    asm volatile("stmatrix.sync.aligned.m8n8.x2.trans.shared.b16 [%0], {%1,%2};" ::"r"(addr), "r"(r0), "r"(r1) : "memory");
}
DEVINL void stsm_x4_t(uint32_t addr, uint32_t r0, uint32_t r1, uint32_t r2, uint32_t r3) {
    asm volatile("stmatrix.sync.aligned.m8n8.x4.trans.shared.b16 [%0], {%1,%2,%3,%4};"
                 ::"r"(addr), "r"(r0), "r"(r1), "r"(r2), "r"(r3) : "memory");
}
DEVINL void stsm_x4(uint32_t addr, uint32_t r0, uint32_t r1, uint32_t r2, uint32_t r3) {
    asm volatile("stmatrix.sync.aligned.m8n8.x4.shared.b16 [%0], {%1,%2,%3,%4};"
                 ::"r"(addr), "r"(r0), "r"(r1), "r"(r2), "r"(r3) : "memory");
}
DEVINL void mma16816(float* d, uint32_t a0, uint32_t a1, uint32_t a2, uint32_t a3, uint32_t b0, uint32_t b1) {
    asm volatile(
        "mma.sync.aligned.m16n8k16.row.col.f32.bf16.bf16.f32 {%0,%1,%2,%3}, {%4,%5,%6,%7}, {%8,%9}, {%0,%1,%2,%3};"
        : "+f"(d[0]), "+f"(d[1]), "+f"(d[2]), "+f"(d[3])
        : "r"(a0), "r"(a1), "r"(a2), "r"(a3), "r"(b0), "r"(b1));
}
DEVINL uint32_t pack_bf16(float lo, float hi) {
    uint32_t r;
    asm("cvt.rn.bf16x2.f32 %0, %1, %2;" : "=r"(r) : "f"(hi), "f"(lo));
    return r;
}

DEVINL void wg_fence() { asm volatile("wgmma.fence.sync.aligned;" ::: "memory"); }
DEVINL void wg_commit() { asm volatile("wgmma.commit_group.sync.aligned;" ::: "memory"); }
template <int N> DEVINL void wg_wait() { asm volatile("wgmma.wait_group.sync.aligned %0;" ::"n"(N) : "memory"); }

DEVINL uint32_t desc_lo(uint32_t saddr) { return ((saddr & 0x3FFFF) >> 4) | (1u << 16); }

template <int OFFB>
DEVINL void wgmma_rs_n32(float* d, const uint32_t* a, uint32_t blo) {
    asm volatile(
        "{\n.reg .b64 db;\n.reg .b32 t;\nadd.u32 t, %20, %21;\nmov.b64 db, {t, 0x40000040};\n"
        "wgmma.mma_async.sync.aligned.m64n32k16.f32.bf16.bf16 "
        "{%0,%1,%2,%3,%4,%5,%6,%7,%8,%9,%10,%11,%12,%13,%14,%15}, {%16,%17,%18,%19}, db, 1, 1, 1, 0;\n}\n"
        : "+f"(d[0]), "+f"(d[1]), "+f"(d[2]), "+f"(d[3]), "+f"(d[4]), "+f"(d[5]), "+f"(d[6]), "+f"(d[7]),
          "+f"(d[8]), "+f"(d[9]), "+f"(d[10]), "+f"(d[11]), "+f"(d[12]), "+f"(d[13]), "+f"(d[14]), "+f"(d[15])
        : "r"(a[0]), "r"(a[1]), "r"(a[2]), "r"(a[3]), "r"(blo), "n"(OFFB));
}
template <int OFFA, int OFFB>
DEVINL void wgmma_ss_n32_ta(float* d, uint32_t alo, uint32_t blo) {
    asm volatile(
        "{\n.reg .b64 da, db;\n.reg .b32 t, u;\nadd.u32 t, %16, %18;\nadd.u32 u, %17, %19;\n"
        "mov.b64 da, {t, 0x40000040};\nmov.b64 db, {u, 0x40000040};\n"
        "wgmma.mma_async.sync.aligned.m64n32k16.f32.bf16.bf16 "
        "{%0,%1,%2,%3,%4,%5,%6,%7,%8,%9,%10,%11,%12,%13,%14,%15}, da, db, 1, 1, 1, 1, 0;\n}\n"
        : "+f"(d[0]), "+f"(d[1]), "+f"(d[2]), "+f"(d[3]), "+f"(d[4]), "+f"(d[5]), "+f"(d[6]), "+f"(d[7]),
          "+f"(d[8]), "+f"(d[9]), "+f"(d[10]), "+f"(d[11]), "+f"(d[12]), "+f"(d[13]), "+f"(d[14]), "+f"(d[15])
        : "r"(alo), "r"(blo), "n"(OFFA), "n"(OFFB));
}
template <int OFFB>
DEVINL void wgmma_rs_n8(float* d, const uint32_t* a, uint32_t blo) {
    asm volatile(
        "{\n.reg .b64 db;\n.reg .b32 t;\nadd.u32 t, %8, %9;\nmov.b64 db, {t, 0x40000040};\n"
        "wgmma.mma_async.sync.aligned.m64n8k16.f32.bf16.bf16 {%0,%1,%2,%3}, {%4,%5,%6,%7}, db, 1, 1, 1, 0;\n}\n"
        : "+f"(d[0]), "+f"(d[1]), "+f"(d[2]), "+f"(d[3])
        : "r"(a[0]), "r"(a[1]), "r"(a[2]), "r"(a[3]), "r"(blo), "n"(OFFB));
}
template <int OFFA, int OFFB>
DEVINL void wgmma_ss_n8_ta(float* d, uint32_t alo, uint32_t blo) {
    asm volatile(
        "{\n.reg .b64 da, db;\n.reg .b32 t, u;\nadd.u32 t, %4, %6;\nadd.u32 u, %5, %7;\n"
        "mov.b64 da, {t, 0x40000040};\nmov.b64 db, {u, 0x40000040};\n"
        "wgmma.mma_async.sync.aligned.m64n8k16.f32.bf16.bf16 {%0,%1,%2,%3}, da, db, 1, 1, 1, 1, 0;\n}\n"
        : "+f"(d[0]), "+f"(d[1]), "+f"(d[2]), "+f"(d[3])
        : "r"(alo), "r"(blo), "n"(OFFA), "n"(OFFB));
}

template <int OFFA, int OFFB>
DEVINL void wgmma_ss_n8_ta_bns(float* d, uint32_t alo, uint32_t blo) {
    asm volatile(
        "{\n.reg .b64 da, db;\n.reg .b32 t, u;\nadd.u32 t, %4, %6;\nadd.u32 u, %5, %7;\n"
        "mov.b64 da, {t, 0x40000040};\nmov.b64 db, {u, 0x00000008};\n"
        "wgmma.mma_async.sync.aligned.m64n8k16.f32.bf16.bf16 {%0,%1,%2,%3}, da, db, 1, 1, 1, 1, 0;\n}\n"
        : "+f"(d[0]), "+f"(d[1]), "+f"(d[2]), "+f"(d[3])
        : "r"(alo), "r"(blo), "n"(OFFA), "n"(OFFB));
}

template <int I, int N, typename F>
DEVINL void static_for(F&& f) {
    if constexpr (I < N) {
        f(std::integral_constant<int, I>{});
        static_for<I + 1, N>(f);
    }
}

DEVINL uint32_t mapa(uint32_t addr, uint32_t rank) {
    uint32_t r;
    asm("mapa.shared::cluster.u32 %0, %1, %2;" : "=r"(r) : "r"(addr), "r"(rank));
    return r;
}
DEVINL void st_async_v2f(uint32_t addr, float x, float y, uint32_t bar) {
    asm volatile("st.async.weak.shared::cluster.mbarrier::complete_tx::bytes.v2.f32 [%0], {%1,%2}, [%3];"
                 ::"r"(addr), "f"(x), "f"(y), "r"(bar) : "memory");
}
DEVINL uint4 ld_relaxed_v4(const void* p) {
    uint4 v;
    asm volatile("ld.relaxed.gpu.global.v4.u32 {%0,%1,%2,%3}, [%4];"
                 : "=r"(v.x), "=r"(v.y), "=r"(v.z), "=r"(v.w) : "l"(p) : "memory");
    return v;
}
DEVINL void st_relaxed_v4(void* p, uint32_t x, uint32_t y, uint32_t z, uint32_t w) {
    asm volatile("st.relaxed.gpu.global.v4.u32 [%0], {%1,%2,%3,%4};" ::"l"(p), "r"(x), "r"(y), "r"(z), "r"(w) : "memory");
}
DEVINL void st_relaxed_u32(void* p, uint32_t x) {
    asm volatile("st.relaxed.gpu.global.u32 [%0], %1;" ::"l"(p), "r"(x) : "memory");
}
DEVINL void stg128(void* p, uint4 v) {
    asm volatile("st.global.v4.u32 [%0], {%1,%2,%3,%4};" ::"l"(p), "r"(v.x), "r"(v.y), "r"(v.z), "r"(v.w) : "memory");
}
DEVINL uint4 lds128(uint32_t a) {
    uint4 v;
    asm volatile("ld.shared.v4.u32 {%0,%1,%2,%3}, [%4];" : "=r"(v.x), "=r"(v.y), "=r"(v.z), "=r"(v.w) : "r"(a) : "memory");
    return v;
}
DEVINL void sts128(uint32_t a, uint4 v) {
    asm volatile("st.shared.v4.u32 [%0], {%1,%2,%3,%4};" ::"r"(a), "r"(v.x), "r"(v.y), "r"(v.z), "r"(v.w) : "memory");
}
DEVINL float2 lds64f(uint32_t a) {
    float2 v;
    asm volatile("ld.shared.v2.f32 {%0,%1}, [%2];" : "=f"(v.x), "=f"(v.y) : "r"(a) : "memory");
    return v;
}
template <int N> DEVINL void reg_inc() { asm volatile("setmaxnreg.inc.sync.aligned.u32 %0;" ::"n"(N)); }
template <int N> DEVINL void reg_dec() { asm volatile("setmaxnreg.dec.sync.aligned.u32 %0;" ::"n"(N)); }

DEVINL void wgmma_ss_n64_tb(float* d, uint32_t alo, uint32_t blo) {
    asm volatile(
        "{\n.reg .b64 da, db;\n"
        "mov.b64 da, {%32, 0x40000040};\nmov.b64 db, {%33, 0x40000040};\n"
        "wgmma.mma_async.sync.aligned.m64n64k16.f32.bf16.bf16 "
        "{%0,%1,%2,%3,%4,%5,%6,%7,%8,%9,%10,%11,%12,%13,%14,%15,%16,%17,%18,%19,%20,%21,%22,%23,%24,%25,%26,%27,%28,%29,%30,%31}, da, db, 1, 1, 1, 0, 1;\n}\n"
        : "+f"(d[0]), "+f"(d[1]), "+f"(d[2]), "+f"(d[3]), "+f"(d[4]), "+f"(d[5]), "+f"(d[6]), "+f"(d[7]),
          "+f"(d[8]), "+f"(d[9]), "+f"(d[10]), "+f"(d[11]), "+f"(d[12]), "+f"(d[13]), "+f"(d[14]), "+f"(d[15]),
          "+f"(d[16]), "+f"(d[17]), "+f"(d[18]), "+f"(d[19]), "+f"(d[20]), "+f"(d[21]), "+f"(d[22]), "+f"(d[23]),
          "+f"(d[24]), "+f"(d[25]), "+f"(d[26]), "+f"(d[27]), "+f"(d[28]), "+f"(d[29]), "+f"(d[30]), "+f"(d[31])
        : "r"(alo), "r"(blo));
}

DEVINL void wgmma_ss_n128_tb(float* d, uint32_t alo, uint32_t blo) {
    asm volatile(
        "{\n.reg .b64 da, db;\n"
        "mov.b64 da, {%64, 0x40000040};\nmov.b64 db, {%65, 0x40000040};\n"
        "wgmma.mma_async.sync.aligned.m64n128k16.f32.bf16.bf16 "
        "{%0,%1,%2,%3,%4,%5,%6,%7,%8,%9,%10,%11,%12,%13,%14,%15,%16,%17,%18,%19,%20,%21,%22,%23,%24,%25,%26,%27,%28,%29,%30,%31,%32,%33,%34,%35,%36,%37,%38,%39,%40,%41,%42,%43,%44,%45,%46,%47,%48,%49,%50,%51,%52,%53,%54,%55,%56,%57,%58,%59,%60,%61,%62,%63}, da, db, 1, 1, 1, 0, 1;\n}\n"
        : "+f"(d[0]), "+f"(d[1]), "+f"(d[2]), "+f"(d[3]), "+f"(d[4]), "+f"(d[5]), "+f"(d[6]), "+f"(d[7]),
          "+f"(d[8]), "+f"(d[9]), "+f"(d[10]), "+f"(d[11]), "+f"(d[12]), "+f"(d[13]), "+f"(d[14]), "+f"(d[15]),
          "+f"(d[16]), "+f"(d[17]), "+f"(d[18]), "+f"(d[19]), "+f"(d[20]), "+f"(d[21]), "+f"(d[22]), "+f"(d[23]),
          "+f"(d[24]), "+f"(d[25]), "+f"(d[26]), "+f"(d[27]), "+f"(d[28]), "+f"(d[29]), "+f"(d[30]), "+f"(d[31]),
          "+f"(d[32]), "+f"(d[33]), "+f"(d[34]), "+f"(d[35]), "+f"(d[36]), "+f"(d[37]), "+f"(d[38]), "+f"(d[39]),
          "+f"(d[40]), "+f"(d[41]), "+f"(d[42]), "+f"(d[43]), "+f"(d[44]), "+f"(d[45]), "+f"(d[46]), "+f"(d[47]),
          "+f"(d[48]), "+f"(d[49]), "+f"(d[50]), "+f"(d[51]), "+f"(d[52]), "+f"(d[53]), "+f"(d[54]), "+f"(d[55]),
          "+f"(d[56]), "+f"(d[57]), "+f"(d[58]), "+f"(d[59]), "+f"(d[60]), "+f"(d[61]), "+f"(d[62]), "+f"(d[63])
        : "r"(alo), "r"(blo));
}

DEVINL void wgmma_ss_n256_tb(float* d, uint32_t alo, uint32_t blo) {
    asm volatile(
        "{\n.reg .b64 da, db;\n"
        "mov.b64 da, {%128, 0x40000040};\nmov.b64 db, {%129, 0x40000040};\n"
        "wgmma.mma_async.sync.aligned.m64n256k16.f32.bf16.bf16 "
        "{%0,%1,%2,%3,%4,%5,%6,%7,%8,%9,%10,%11,%12,%13,%14,%15,%16,%17,%18,%19,%20,%21,%22,%23,%24,%25,%26,%27,%28,%29,%30,%31,%32,%33,%34,%35,%36,%37,%38,%39,%40,%41,%42,%43,%44,%45,%46,%47,%48,%49,%50,%51,%52,%53,%54,%55,%56,%57,%58,%59,%60,%61,%62,%63,%64,%65,%66,%67,%68,%69,%70,%71,%72,%73,%74,%75,%76,%77,%78,%79,%80,%81,%82,%83,%84,%85,%86,%87,%88,%89,%90,%91,%92,%93,%94,%95,%96,%97,%98,%99,%100,%101,%102,%103,%104,%105,%106,%107,%108,%109,%110,%111,%112,%113,%114,%115,%116,%117,%118,%119,%120,%121,%122,%123,%124,%125,%126,%127}, da, db, 1, 1, 1, 0, 1;\n}\n"
        : "+f"(d[0]), "+f"(d[1]), "+f"(d[2]), "+f"(d[3]), "+f"(d[4]), "+f"(d[5]), "+f"(d[6]), "+f"(d[7]),
          "+f"(d[8]), "+f"(d[9]), "+f"(d[10]), "+f"(d[11]), "+f"(d[12]), "+f"(d[13]), "+f"(d[14]), "+f"(d[15]),
          "+f"(d[16]), "+f"(d[17]), "+f"(d[18]), "+f"(d[19]), "+f"(d[20]), "+f"(d[21]), "+f"(d[22]), "+f"(d[23]),
          "+f"(d[24]), "+f"(d[25]), "+f"(d[26]), "+f"(d[27]), "+f"(d[28]), "+f"(d[29]), "+f"(d[30]), "+f"(d[31]),
          "+f"(d[32]), "+f"(d[33]), "+f"(d[34]), "+f"(d[35]), "+f"(d[36]), "+f"(d[37]), "+f"(d[38]), "+f"(d[39]),
          "+f"(d[40]), "+f"(d[41]), "+f"(d[42]), "+f"(d[43]), "+f"(d[44]), "+f"(d[45]), "+f"(d[46]), "+f"(d[47]),
          "+f"(d[48]), "+f"(d[49]), "+f"(d[50]), "+f"(d[51]), "+f"(d[52]), "+f"(d[53]), "+f"(d[54]), "+f"(d[55]),
          "+f"(d[56]), "+f"(d[57]), "+f"(d[58]), "+f"(d[59]), "+f"(d[60]), "+f"(d[61]), "+f"(d[62]), "+f"(d[63]),
          "+f"(d[64]), "+f"(d[65]), "+f"(d[66]), "+f"(d[67]), "+f"(d[68]), "+f"(d[69]), "+f"(d[70]), "+f"(d[71]),
          "+f"(d[72]), "+f"(d[73]), "+f"(d[74]), "+f"(d[75]), "+f"(d[76]), "+f"(d[77]), "+f"(d[78]), "+f"(d[79]),
          "+f"(d[80]), "+f"(d[81]), "+f"(d[82]), "+f"(d[83]), "+f"(d[84]), "+f"(d[85]), "+f"(d[86]), "+f"(d[87]),
          "+f"(d[88]), "+f"(d[89]), "+f"(d[90]), "+f"(d[91]), "+f"(d[92]), "+f"(d[93]), "+f"(d[94]), "+f"(d[95]),
          "+f"(d[96]), "+f"(d[97]), "+f"(d[98]), "+f"(d[99]), "+f"(d[100]), "+f"(d[101]), "+f"(d[102]), "+f"(d[103]),
          "+f"(d[104]), "+f"(d[105]), "+f"(d[106]), "+f"(d[107]), "+f"(d[108]), "+f"(d[109]), "+f"(d[110]), "+f"(d[111]),
          "+f"(d[112]), "+f"(d[113]), "+f"(d[114]), "+f"(d[115]), "+f"(d[116]), "+f"(d[117]), "+f"(d[118]), "+f"(d[119]),
          "+f"(d[120]), "+f"(d[121]), "+f"(d[122]), "+f"(d[123]), "+f"(d[124]), "+f"(d[125]), "+f"(d[126]), "+f"(d[127])
        : "r"(alo), "r"(blo));
}

constexpr int DH = 192, DM = 640, NMEM = 8, SEG = 32, NSEG = 64, HD = 6144, SEQ = 2048;

__device__ bf16 g_Qx[SEQ * HD];
__device__ bf16 g_Kx[SEQ * HD];
__device__ bf16 g_Vx[SEQ * HD];
__device__ bf16 g_Km[NSEG * NMEM * HD];
__device__ bf16 g_Vm[NSEG * NMEM * HD];
__device__ uint32_t g_PA[3 * 96 * 32 * 32];
__device__ uint32_t g_P2[4 * 80 * 7 * 32];
constexpr int MBREP = 2;
__device__ uint32_t g_MB[4 * MBREP * 3072];

constexpr int FF = 1536, KCAT = HD + FF;

__device__ bf16 g_Acat[SEQ * KCAT];
__device__ float g_gate[SEQ];
__device__ float g_acc[SEQ * DM];
__device__ unsigned g_epoch;
__device__ unsigned g_ticket;
__device__ unsigned g_segcnt[65];
__device__ unsigned g_exit;
__device__ unsigned g_wflag;
__device__ unsigned g_gflag[16];
__device__ unsigned g_hflag[16 * 2];
__device__ unsigned g_cflag[64 * 8];
__device__ unsigned g_aflag[16 * 8];
__device__ unsigned g_oflag[16 * 5];

DEVINL unsigned ld_acquire(const unsigned* p) {
    unsigned v;
    asm volatile("ld.acquire.gpu.global.u32 %0, [%1];" : "=r"(v) : "l"(p) : "memory");
    return v;
}
DEVINL void wait_flag(const unsigned* p, unsigned target) {
    unsigned n = 0;
    while ((int)(ld_acquire(p) - target) < 0) {
        __nanosleep(64);
        if (++n > (1u << 24)) break;
    }
}
DEVINL void fence_gpu() { asm volatile("fence.acq_rel.gpu;" ::: "memory"); }
DEVINL void signal_flag(unsigned* p) {
    fence_gpu();
    atomicAdd(p, 1u);
}

DEVINL float ex2(float x) { float r; asm("ex2.approx.ftz.f32 %0, %1;" : "=f"(r) : "f"(x)); return r; }
DEVINL float rcpf(float x) { float r; asm("rcp.approx.ftz.f32 %0, %1;" : "=f"(r) : "f"(x)); return r; }

namespace csmall {
#define POLL_LIMIT (1u << 18)
namespace ch {
constexpr int OFF_WV = 0;
constexpr int OFF_WO = 81920;
constexpr int WO_A = 0, WO_B = 24576, WO_C = 43008, WO_E = 67584;
constexpr int OFF_X = 163840;
constexpr int OFF_MEM = 204800;
constexpr int OFF_K = 215040;
constexpr int OFF_V = 220160;
constexpr int OFF_S = 225280;
constexpr int OFF_BAR = OFF_S + 3840;
constexpr int OFF_O = 229376;
constexpr int OFF_QM = 157696;
constexpr int OFF_Q = 158720;
constexpr int SMEM_BYTES = OFF_O + 3072;
constexpr int BAR_W1 = 0, BAR_W2 = 8, BAR_X = 16, BAR_S = 24, BAR_O = 32, BAR_W3 = 40, BAR_OL = 48, BAR_C = 56;
constexpr int NB_MEM = 1, NB_QK = 2, NB_OUT = 3, NB_WG1 = 4, NB_WG2 = 5, NB_V = 6, NB_QK2 = 7, NB_KX = 8, NB_WO = 9, NB_WG0 = 10;
}

DEVINL int vcta() { int t; asm volatile("mov.u32 %0, %%ctaid.x;" : "=r"(t)); return t; }
DEVINL uint32_t vrank() { uint32_t r; asm volatile("mov.u32 %0, %%cluster_ctarank;" : "=r"(r)); return r; }
DEVINL int vhead() { return vcta() / 3; }
DEVINL int vtid() { int t; asm volatile("mov.u32 %0, %%tid.x;" : "=r"(t)); return t; }

template <int NKS>
DEVINL void load_afrags(uint32_t (&W)[NKS][4], uint32_t tile, int warp, int lane) {
    const int mid = lane >> 3, i = lane & 7;
    const uint32_t base = tile + ((mid >> 1) * 8 + i) * 128 + (((2 * warp + (mid & 1)) ^ i) << 4);
#pragma unroll
    for (int ks = 0; ks < NKS; ks++) ldsm_x4_t(W[ks][0], W[ks][1], W[ks][2], W[ks][3], base + ks * 2048);
}

DEVINL void mem_part_regs(float (&acc)[4], const uint32_t (&W)[40][4], uint32_t sXM, uint32_t barC, uint32_t par) {
    const int lane = vtid() & 31;
    float c1[4] = {0.f, 0.f, 0.f, 0.f}, c2[4] = {0.f, 0.f, 0.f, 0.f}, c3[4] = {0.f, 0.f, 0.f, 0.f};
    acc[0] = acc[1] = acc[2] = acc[3] = 0.f;
    const int mid = lane >> 3, tok = lane & 7;
    const uint32_t a0 = sXM + mid * 128 + tok * 16;
    const uint32_t a1 = a0 + 512;
    uint32_t b[2][8];
    constexpr int order[10] = {1, 4, 7, 2, 5, 8, 0, 3, 6, 9};
    mbar_wait(barC + 8, par);
    ldsm_x4(b[0][0], b[0][1], b[0][2], b[0][3], a0 + 1024);
    ldsm_x4(b[0][4], b[0][5], b[0][6], b[0][7], a1 + 1024);
#pragma unroll
    for (int n = 0; n < 10; n++) {
        const int c = order[n];
        if (n < 9) {
            const int cn = order[n + 1];
            if (n + 1 == 3) mbar_wait(barC + 16, par);
            if (n + 1 == 6) mbar_wait(barC, par);
            ldsm_x4(b[(n + 1) & 1][0], b[(n + 1) & 1][1], b[(n + 1) & 1][2], b[(n + 1) & 1][3], a0 + cn * 1024);
            ldsm_x4(b[(n + 1) & 1][4], b[(n + 1) & 1][5], b[(n + 1) & 1][6], b[(n + 1) & 1][7], a1 + cn * 1024);
        }
        mma16816(acc, W[4 * c][0], W[4 * c][1], W[4 * c][2], W[4 * c][3], b[n & 1][0], b[n & 1][1]);
        mma16816(c1, W[4 * c + 1][0], W[4 * c + 1][1], W[4 * c + 1][2], W[4 * c + 1][3], b[n & 1][2], b[n & 1][3]);
        mma16816(c2, W[4 * c + 2][0], W[4 * c + 2][1], W[4 * c + 2][2], W[4 * c + 2][3], b[n & 1][4], b[n & 1][5]);
        mma16816(c3, W[4 * c + 3][0], W[4 * c + 3][1], W[4 * c + 3][2], W[4 * c + 3][3], b[n & 1][6], b[n & 1][7]);
    }
#pragma unroll
    for (int i = 0; i < 4; i++) acc[i] = (acc[i] + c1[i]) + (c2[i] + c3[i]);
}

DEVINL void store_memT(uint32_t rows, const float (&acc)[4]) {
    const int tt = vtid(), warp = (tt >> 5) & 3, lane = tt & 31;
    const uint32_t r0 = pack_bf16(acc[0], acc[1]), r1 = pack_bf16(acc[2], acc[3]);
    const int i = lane & 7, half = (lane >> 3) & 1;
    stsm_x2_t(rows + i * 128 + (((2 * warp + half) ^ i) << 4), r0, r1);
}

DEVINL void store_xT(uint32_t rows, const float (&d)[16]) {
    const int tt = vtid(), warp = (tt >> 5) & 3, lane = tt & 31;
    const int i = lane & 7, mid = lane >> 3;
    const int half = mid & 1, jj = mid >> 1;
    const uint32_t base = rows + (jj * 8 + i) * 128 + (((2 * warp + half) ^ i) << 4);
#pragma unroll
    for (int q = 0; q < 2; q++) {
        const int j0 = 2 * q, j1 = 2 * q + 1;
        const uint32_t r0 = pack_bf16(d[4 * j0 + 0], d[4 * j0 + 1]);
        const uint32_t r1 = pack_bf16(d[4 * j0 + 2], d[4 * j0 + 3]);
        const uint32_t r2 = pack_bf16(d[4 * j1 + 0], d[4 * j1 + 1]);
        const uint32_t r3 = pack_bf16(d[4 * j1 + 2], d[4 * j1 + 3]);
        stsm_x4_t(base + q * 2048, r0, r1, r2, r3);
    }
}

template <int NROWS>
DEVINL void copy_rows_out(uint32_t rows, bf16* gdst) {
    const int t = vtid() & 127;
    const int row = t >> 3, slot = t & 7;
    const uint32_t src = rows + row * 128 + ((slot ^ (row & 7)) << 4);
    bf16* dst = gdst + row * HD + slot * 8;
#pragma unroll
    for (int it = 0; it < (NROWS + 15) / 16; it++) {
        if (NROWS >= 16 * (it + 1) || row + 16 * it < NROWS) stg128(dst + it * 16 * HD, lds128(src + it * 2048));
    }
}

DEVINL uint32_t* partial_ptr(int slot, int u0, int ustep, int h) {
    const int tt = vtid(), warp = (tt >> 5) & 3, lane = tt & 31;
    return g_PA + ((slot * 96 + u0 + 2 * warp * ustep) * 32 + h) * 32 + lane;
}
DEVINL void store_partial(const float (&acc)[4], uint32_t* p, int ustep) {
    uint32_t v0 = pack_bf16(acc[0], acc[1]), v1 = pack_bf16(acc[2], acc[3]);
    v0 = v0 ? v0 : 0x00008000u;
    v1 = v1 ? v1 : 0x00008000u;
    st_relaxed_u32(p, v0);
    st_relaxed_u32(p + ustep * 1024, v1);
}

DEVINL void x_part_rs(float (&d)[16], const uint32_t (&W)[40][4], uint32_t sXM) {
#pragma unroll
    for (int i = 0; i < 16; i++) d[i] = 0.f;
    const uint32_t blo = desc_lo(sXM);
    wg_fence();
    static_for<0, 40>([&](auto I) {
        constexpr int ks = decltype(I)::value;
        wgmma_rs_n32<(((ks >> 2) * 4096 + (ks & 3) * 32) >> 4)>(d, W[ks], blo);
    });
    wg_commit();
    wg_wait<0>();
}

#define VX_GROUP 4
DEVINL void x_part_ss(float (&d)[16], uint32_t sW, uint32_t sXM) {
#pragma unroll
    for (int i = 0; i < 16; i++) d[i] = 0.f;
    const uint32_t alo = desc_lo(sW), blo = desc_lo(sXM);
#pragma unroll 1
    for (int p = 0; p < 40 / VX_GROUP; p++) {
        wg_fence();
        static_for<0, VX_GROUP>([&](auto I) {
            constexpr int ks = decltype(I)::value;
            wgmma_ss_n32_ta<((ks * 2048) >> 4), (((ks >> 2) * 4096 + (ks & 3) * 32) >> 4)>(d, alo + p * (VX_GROUP * 128), blo + p * (VX_GROUP / 4 * 256));
        });
        wg_commit();
        wg_wait<0>();
    }
}

DEVINL void wo_chunk_ss(float (&acc)[4], uint32_t alo, uint32_t blo, uint32_t q) {
    const uint32_t a = alo + q * 512, b = blo + q * 64;
    wgmma_ss_n8_ta<0, 0>(acc, a, b);
    wgmma_ss_n8_ta<128, 2>(acc, a, b);
    wgmma_ss_n8_ta<256, 4>(acc, a, b);
    wgmma_ss_n8_ta<384, 6>(acc, a, b);
}
DEVINL void wo_tile_ss(float (&acc)[4], uint32_t tile, uint32_t sO, uint32_t barOL, uint32_t barO, uint32_t par) {
    const uint32_t rk = vrank(), alo = desc_lo(tile), blo = desc_lo(sO);
    acc[0] = acc[1] = acc[2] = acc[3] = 0.f;
    mbar_wait(barOL, par);
    wg_fence();
    wo_chunk_ss(acc, alo, blo, rk);
    wg_commit();
    mbar_wait(barO, par);
    wg_fence();
    wo_chunk_ss(acc, alo, blo, rk == 0 ? 1 : 0);
    wo_chunk_ss(acc, alo, blo, rk == 2 ? 1 : 2);
    wg_commit();
    wg_wait<0>();
}

DEVINL void wo_chunk_mixed3(float (&acc)[4], const uint32_t (&WO)[3][4], uint32_t hlo, uint32_t blo, uint32_t q) {
    if (q == 0) {
        wgmma_ss_n8_ta<0, 6>(acc, hlo, blo);
        wgmma_rs_n8<0>(acc, WO[0], blo);
        wgmma_rs_n8<2>(acc, WO[1], blo);
        wgmma_rs_n8<4>(acc, WO[2], blo);
    } else {
        wo_chunk_ss(acc, hlo - 384, blo, q);
    }
}
DEVINL void wo_tile_mixed3(float (&acc)[4], const uint32_t (&WO)[3][4], uint32_t hi, uint32_t sO, uint32_t barOL, uint32_t barO, uint32_t par) {
    const uint32_t rk = vrank(), hlo = desc_lo(hi), blo = desc_lo(sO);
    acc[0] = acc[1] = acc[2] = acc[3] = 0.f;
    mbar_wait(barOL, par);
    wg_fence();
    wo_chunk_mixed3(acc, WO, hlo, blo, rk);
    wg_commit();
    mbar_wait(barO, par);
    wg_fence();
    wo_chunk_mixed3(acc, WO, hlo, blo, rk == 0 ? 1 : 0);
    wo_chunk_mixed3(acc, WO, hlo, blo, rk == 2 ? 1 : 2);
    wg_commit();
    wg_wait<0>();
}

DEVINL void issue_x_load(uint32_t sb, const CUtensorMap* tmX, int seg) {
    const int tt = vtid(), warp = (tt >> 5) & 3;
    if ((tt & 31) == 0) {
        if (warp == 0) mbar_expect_tx(sb + ch::OFF_BAR + ch::BAR_X, 40960);
        const int i = (int)vrank() + 3 * warp;
        if (i < 10)
            asm volatile(
                "cp.async.bulk.tensor.2d.shared::cluster.global.mbarrier::complete_tx::bytes.multicast::cluster [%0], [%1, {%3, %4}], [%2], %5;"
                ::"r"(sb + ch::OFF_X + i * 4096), "l"(tmX), "r"(sb + ch::OFF_BAR + ch::BAR_X), "r"(i * 64), "r"(seg * SEG), "h"((uint16_t)7) : "memory");
    }
}

DEVINL void store_tile_tma(uint32_t src, const CUtensorMap* m, int c0, int seg) {
    asm volatile("cp.async.bulk.tensor.2d.global.shared::cta.bulk_group [%0, {%2, %3}], [%1];" ::"l"(m), "r"(src), "r"(c0), "r"(seg * SEG) : "memory");
}
DEVINL void bulk_commit() { asm volatile("cp.async.bulk.commit_group;" ::: "memory"); }

DEVINL void recycle_slots(int s) {
    const int b = vcta();
    const int t = vtid() & 127;
    uint32_t* src = g_PA + (((s + 2) % 3) * 96 + b) * 1024 + t * 4;
    st_relaxed_v4(src, 0u, 0u, 0u, 0u);
    st_relaxed_v4(src + 512, 0u, 0u, 0u, 0u);
    if (t < 32 * MBREP) st_relaxed_u32(g_MB + (((s + 3) & 3) * MBREP + (t >> 5)) * 3072 + b * 32 + (t & 31), 0u);
}

#define DELAY_A 250
#define DELAY_B 350
DEVINL void spin_cycles(uint32_t n) {
    uint32_t t0, t1;
    asm volatile("mov.u32 %0, %%clock;" : "=r"(t0));
    do { asm volatile("mov.u32 %0, %%clock;" : "=r"(t1)); } while (t1 - t0 < n);
}
DEVINL float bf_lo(uint32_t w) { return __uint_as_float(w << 16); }
DEVINL float bf_hi(uint32_t w) { return __uint_as_float(w & 0xffff0000u); }
DEVINL uint32_t ld_relaxed_u32(const void* p) {
    uint32_t v;
    asm volatile("ld.relaxed.gpu.global.u32 %0, [%1];" : "=r"(v) : "l"(p) : "memory");
    return v;
}

DEVINL void reduce_partials(int s, uint32_t sRed) {
    const int u = vcta(), tt = vtid(), lane = tt & 31, warp = (tt >> 5) & 3;
    const uint32_t* src = g_PA + ((s % 3) * 96 + u) * 1024 + warp * 256 + lane;
    uint32_t v[8];
#pragma unroll
    for (int i = 0; i < 8; i++) v[i] = ld_relaxed_u32(src + i * 32);
    uint32_t n = 0;
    while (true) {
        bool ok = true;
#pragma unroll
        for (int i = 0; i < 8; i++) {
            if (v[i] == 0) { v[i] = ld_relaxed_u32(src + i * 32); ok = false; }
        }
        if (ok) break;
        if (++n > POLL_LIMIT) break;
    }
    const float lo = ((bf_lo(v[0]) + bf_lo(v[1])) + (bf_lo(v[2]) + bf_lo(v[3]))) + ((bf_lo(v[4]) + bf_lo(v[5])) + (bf_lo(v[6]) + bf_lo(v[7])));
    const float hi = ((bf_hi(v[0]) + bf_hi(v[1])) + (bf_hi(v[2]) + bf_hi(v[3]))) + ((bf_hi(v[4]) + bf_hi(v[5])) + (bf_hi(v[6]) + bf_hi(v[7])));
    asm volatile("st.shared.v2.f32 [%0], {%1,%2};" ::"r"(sRed + warp * 256 + lane * 8), "f"(lo), "f"(hi) : "memory");
    bar_sync(ch::NB_WG2, 128);
    if (warp < MBREP) {
        const float2 p0 = lds64f(sRed + lane * 8), p1 = lds64f(sRed + 256 + lane * 8);
        const float2 p2 = lds64f(sRed + 512 + lane * 8), p3 = lds64f(sRed + 768 + lane * 8);
        uint32_t word = pack_bf16((p0.x + p1.x) + (p2.x + p3.x), (p0.y + p1.y) + (p2.y + p3.y));
        asm volatile("movmatrix.sync.aligned.m8n8.trans.b16 %0, %0;" : "+r"(word));
        word = word ? word : 0x00008000u;
        st_relaxed_u32(g_MB + (((s + 1) & 3) * MBREP + warp) * 3072 + u * 32 + lane, word);
    }
}

DEVINL void bulk_to_peer(uint32_t src, uint32_t bar, uint32_t r) {
    asm volatile("cp.async.bulk.shared::cluster.shared::cta.mbarrier::complete_tx::bytes [%0], [%1], 1024, [%2];"
                 ::"r"(mapa(src, r)), "r"(src), "r"(mapa(bar, r)) : "memory");
}
DEVINL uint32_t add3_bf16x2(uint32_t a, uint32_t b, uint32_t c) {
    return pack_bf16(bf_lo(a) + bf_lo(b) + bf_lo(c), bf_hi(a) + bf_hi(b) + bf_hi(c));
}
DEVINL bool vec_ok(const uint4& v) { return v.x && v.y && v.z && v.w; }

DEVINL void gather_memory(int s, uint32_t sb, uint32_t rank) {
    const int tt = vtid(), lane = tt & 31, warp = (tt >> 5) & 3;
    const int chunk = rank + 3 * warp;
    if (chunk < 10) {
        const uint32_t* base = g_MB + (((s + 1) & 3) * MBREP + ((vcta() / 3) & (MBREP - 1))) * 3072;
        const uint32_t dst = sb + ch::OFF_MEM + chunk * 1024 + lane * 16;
        const uint32_t off0 = 0, off1 = 512;
        uint32_t n = 0;
        if (chunk < 9) {
            const uint32_t* src = base + chunk * 256 + lane * 4;
            uint4 v0 = ld_relaxed_v4(src), v1 = ld_relaxed_v4(src + 128);
            while (true) {
                const bool k0 = vec_ok(v0), k1 = vec_ok(v1);
                if (k0 && k1) break;
                if (!k0) v0 = ld_relaxed_v4(src);
                if (!k1) v1 = ld_relaxed_v4(src + 128);
                if (++n > POLL_LIMIT) break;
            }
            sts128(dst + off0, v0);
            sts128(dst + off1, v1);
        } else {
            const uint32_t* s9 = base + (72 + 3 * (lane >> 3)) * 32 + (lane & 7) * 4;
            uint4 e0 = ld_relaxed_v4(s9), e1 = ld_relaxed_v4(s9 + 32), e2 = ld_relaxed_v4(s9 + 64);
            uint4 f0 = ld_relaxed_v4(s9 + 384), f1 = ld_relaxed_v4(s9 + 416), f2 = ld_relaxed_v4(s9 + 448);
            while (true) {
                const bool k0 = vec_ok(e0), k1 = vec_ok(e1), k2 = vec_ok(e2), j0 = vec_ok(f0), j1 = vec_ok(f1), j2 = vec_ok(f2);
                if (k0 && k1 && k2 && j0 && j1 && j2) break;
                if (!k0) e0 = ld_relaxed_v4(s9);
                if (!k1) e1 = ld_relaxed_v4(s9 + 32);
                if (!k2) e2 = ld_relaxed_v4(s9 + 64);
                if (!j0) f0 = ld_relaxed_v4(s9 + 384);
                if (!j1) f1 = ld_relaxed_v4(s9 + 416);
                if (!j2) f2 = ld_relaxed_v4(s9 + 448);
                if (++n > POLL_LIMIT) break;
            }
            sts128(dst + off0, make_uint4(add3_bf16x2(e0.x, e1.x, e2.x), add3_bf16x2(e0.y, e1.y, e2.y),
                                          add3_bf16x2(e0.z, e1.z, e2.z), add3_bf16x2(e0.w, e1.w, e2.w)));
            sts128(dst + off1, make_uint4(add3_bf16x2(f0.x, f1.x, f2.x), add3_bf16x2(f0.y, f1.y, f2.y),
                                          add3_bf16x2(f0.z, f1.z, f2.z), add3_bf16x2(f0.w, f1.w, f2.w)));
        }
        fence_proxy_async();
        __syncwarp();
        if (lane == 0) {
            const uint32_t bar = sb + ch::OFF_BAR + ch::BAR_C + rank * 8;
            const uint32_t src = sb + ch::OFF_MEM + chunk * 1024;
            mbar_arrive(bar);
            bulk_to_peer(src, bar, rank == 0 ? 1 : 0);
            bulk_to_peer(src, bar, rank == 2 ? 1 : 2);
        }
    }
}

__global__ void __launch_bounds__(384, 1)
chain_kernel(const __grid_constant__ CUtensorMap tmWq, const __grid_constant__ CUtensorMap tmWk,
             const __grid_constant__ CUtensorMap tmWv, const __grid_constant__ CUtensorMap tmWo,
             const __grid_constant__ CUtensorMap tmWo16, const __grid_constant__ CUtensorMap tmX,
             const __grid_constant__ CUtensorMap tmQo, const __grid_constant__ CUtensorMap tmKo, const __grid_constant__ CUtensorMap tmVo,
             const bf16* __restrict__ mem0, long long* __restrict__ dbg) {
    using namespace ch;
    extern __shared__ __align__(1024) uint8_t smem_raw[];
    const uint32_t sb = smem_u32(smem_raw);
    const int tid = threadIdx.x, wg = tid >> 7;
    uint32_t rank;
    asm("mov.u32 %0, %%cluster_ctarank;" : "=r"(rank));
    const int h = blockIdx.x / 3;
    const int c0 = h * DH + 64 * (int)rank;
    const int tb = 3 * (int)rank;
    const uint32_t bars = sb + OFF_BAR;
    asm volatile("griddepcontrol.launch_dependents;" ::: "memory");

    if (tid == 0) {
        mbar_init(bars + BAR_W1, 3);
        mbar_init(bars + BAR_W2, 1);
        mbar_init(bars + BAR_W3, 1);
        mbar_init(bars + BAR_X, 1);
        mbar_init(bars + BAR_S, 1);
        mbar_init(bars + BAR_O, 1);
        mbar_init(bars + BAR_OL, 1);
        for (int i = 0; i < 3; i++) mbar_init(bars + BAR_C + i * 8, i == (int)rank ? (rank == 0 ? 4 : 3) : 1);
        asm volatile("fence.mbarrier_init.release.cluster;" ::: "memory");
    }
    if ((tid & 31) == 0) {
        const CUtensorMap* m = tid == 0 ? &tmWq : tid == 32 ? &tmWo16 : tid == 64 ? &tmX : tid == 96 ? &tmQo : tid == 128 ? &tmWk
                             : tid == 160 ? &tmWo : tid == 192 ? &tmKo : tid == 224 ? &tmVo : &tmWv;
        asm volatile("prefetch.tensormap [%0];" ::"l"(m) : "memory");
    }
    __syncthreads();
    if (tid == 0) {
        mbar_expect_tx(bars + BAR_W1, 81920);
        for (int i = 0; i < 5; i++) tma_load_2d(sb + OFF_WV + i * 16384, &tmWq, c0, i * 128, bars + BAR_W1);
    } else if (tid == 128) {
        mbar_expect_tx(bars + BAR_W1, 81920);
        for (int i = 0; i < 5; i++) tma_load_2d(sb + OFF_WO + i * 16384, &tmWk, c0, i * 128, bars + BAR_W1);
    } else if (tid == 256) {
        mbar_expect_tx(bars + BAR_W1, 12288);
        tma_load_2d(sb + OFF_X + 12288, &tmWo, (tb + 1) * 64, h * DH, bars + BAR_W1);
        for (int i = 0; i < 5; i++) tma_prefetch_2d(&tmWv, c0, i * 128);
    }

    if (wg == 0) {
        reg_inc<224>();
        uint32_t W[40][4];
        mbar_wait(bars + BAR_W1, 0);
        load_afrags<40>(W, sb + OFF_WV, (tid >> 5) & 3, tid & 31);
        bar_sync(NB_MEM, 384);
        asm volatile("barrier.cluster.arrive.release.aligned; barrier.cluster.wait.acquire.aligned;" ::: "memory");
        {
            float d[16];
            mbar_wait(bars + BAR_X, 0);
            x_part_rs(d, W, sb + OFF_X);
            store_xT(sb + OFF_Q, d);
            mbar_wait(bars + BAR_W2, 0);
            x_part_ss(d, sb + OFF_WV, sb + OFF_X);
            store_xT(sb + OFF_V + 1024, d);
            fence_proxy_async();
            bar_arrive(NB_V, 384);
        }
#pragma unroll 1
        for (int s = 0; s < NSEG - 1; s++) {
            {
                float acc[4];
                mem_part_regs(acc, W, sb + OFF_MEM, bars + BAR_C, s & 1);
                store_memT(sb + OFF_QM, acc);
            }
            bar_arrive(NB_QK, 256);
            bar_sync(NB_KX, 256);
            {
                const int tt = vtid(), lane = tt & 31, j = ((tt >> 5) & 3) + 1;
                const int mid = lane >> 3, i = lane & 7;
                const uint32_t o0 = i * 128 + ((mid ^ i) << 4), o1 = o0 ^ 64;
                uint32_t a[8], b[8];
                ldsm_x4(b[0], b[1], b[2], b[3], sb + OFF_K + j * 1024 + o0);
                ldsm_x4(b[4], b[5], b[6], b[7], sb + OFF_K + j * 1024 + o1);
                ldsm_x4(a[0], a[1], a[2], a[3], sb + OFF_QM + o0);
                ldsm_x4(a[4], a[5], a[6], a[7], sb + OFF_QM + o1);
                float sc[4] = {0.f, 0.f, 0.f, 0.f}, sc1[4] = {0.f, 0.f, 0.f, 0.f};
                mma16816(sc, a[0], 0, a[1], 0, b[0], b[1]);
                mma16816(sc1, a[2], 0, a[3], 0, b[2], b[3]);
                bar_arrive(NB_QK2, 384);
                mma16816(sc, a[4], 0, a[5], 0, b[4], b[5]);
                mma16816(sc1, a[6], 0, a[7], 0, b[6], b[7]);
                const float s0 = sc[0] + sc1[0], s1 = sc[1] + sc1[1];
                const uint32_t dst = sb + OFF_S + (vrank() * 5 + j) * 256 + lane * 8;
#pragma unroll
                for (uint32_t r = 0; r < 3; r++) st_async_v2f(mapa(dst, r), s0, s1, mapa(bars + BAR_S, r));
            }
            if (s > 0) recycle_slots(s);
            if ((vtid() & 127) == 0) {
                asm volatile("cp.async.bulk.wait_group 0;" ::: "memory");
                store_tile_tma(sb + OFF_Q, &tmQo, (vcta() * 64), s);
                store_tile_tma(sb + OFF_K + 1024, &tmKo, (vcta() * 64), s);
                store_tile_tma(sb + OFF_V + 1024, &tmVo, (vcta() * 64), s);
                bulk_commit();
            }
            {
                float acc[4];
                if (s == 0) mbar_wait(bars + BAR_W3, 0);
                uint32_t* pp = partial_ptr(s % 3, (int)vrank() * 24, 1, vhead());
                wo_tile_ss(acc, sb + OFF_WO + WO_A, sb + OFF_O, bars + BAR_OL, bars + BAR_O, s & 1);
                store_partial(acc, pp, 1);
            }
            if ((vtid() & 127) == 0) asm volatile("cp.async.bulk.wait_group.read 0;" ::: "memory");
            bar_sync(NB_WO, 384);
            {
                float d[16];
                mbar_wait(bars + BAR_X, (s + 1) & 1);
                x_part_ss(d, sb + OFF_WV, sb + OFF_X);
                store_xT(sb + OFF_V + 1024, d);
                x_part_rs(d, W, sb + OFF_X);
                store_xT(sb + OFF_Q, d);
                fence_proxy_async();
                if (s + 1 < NSEG - 1) bar_arrive(NB_V, 384);
            }
        }
        bar_arrive(NB_QK2, 384);
        bar_sync(NB_KX, 256);
        bar_sync(NB_WG0, 128);
        if ((vtid() & 127) == 0) {
            asm volatile("cp.async.bulk.wait_group 0;" ::: "memory");
            store_tile_tma(sb + OFF_Q, &tmQo, c0, NSEG - 1);
            store_tile_tma(sb + OFF_K + 1024, &tmKo, c0, NSEG - 1);
            store_tile_tma(sb + OFF_V + 1024, &tmVo, c0, NSEG - 1);
            bulk_commit();
            fence_gpu();
            atomicAdd(&g_cflag[(NSEG - 2) * 8 + (vhead() >> 2)], 1u);
        }
        bar_sync(NB_OUT, 384);
        recycle_slots(NSEG - 1);
        bar_sync(NB_WG0, 128);
        if ((vtid() & 127) == 0) {
            asm volatile("cp.async.bulk.wait_group 0;" ::: "memory");
            fence_gpu();
            atomicAdd(&g_cflag[(NSEG - 1) * 8 + (vhead() >> 2)], 1u);
        }
    } else if (wg == 1) {
        reg_inc<216>();
        uint32_t W[40][4], WO[3][4];
        mbar_wait(bars + BAR_W1, 0);
        load_afrags<40>(W, sb + OFF_WO, (tid >> 5) & 3, tid & 31);
        load_afrags<3>(WO, sb + OFF_X + 12288, (tid >> 5) & 3, tid & 31);
        bar_sync(NB_MEM, 384);
        asm volatile("barrier.cluster.arrive.release.aligned; barrier.cluster.wait.acquire.aligned;" ::: "memory");
        {
            float d[16];
            mbar_wait(bars + BAR_X, 0);
            x_part_rs(d, W, sb + OFF_X);
            store_xT(sb + OFF_K + 1024, d);
            fence_proxy_async();
            bar_arrive(NB_KX, 256);
        }
#pragma unroll 1
        for (int s = 0; s < NSEG; s++) {
            {
                float acc[4];
                mem_part_regs(acc, W, sb + OFF_MEM, bars + BAR_C, s & 1);
                store_memT(sb + OFF_K, acc);
            }
            if (s == NSEG - 1) {
                bar_arrive(NB_QK2, 384);
                bar_sync(NB_WG1, 128);
                copy_rows_out<8>(sb + OFF_K, g_Km + (size_t)s * NMEM * HD + (vcta() * 64));
                bar_arrive(NB_OUT, 384);
                break;
            }
            bar_sync(NB_QK, 256);
            if (((vtid() >> 5) & 3) == 0) {
                const int lane = vtid() & 31;
                const int mid = lane >> 3, i = lane & 7;
                const uint32_t o0 = i * 128 + ((mid ^ i) << 4), o1 = o0 ^ 64;
                uint32_t a[8], b[8];
                ldsm_x4(b[0], b[1], b[2], b[3], sb + OFF_K + o0);
                ldsm_x4(b[4], b[5], b[6], b[7], sb + OFF_K + o1);
                ldsm_x4(a[0], a[1], a[2], a[3], sb + OFF_QM + o0);
                ldsm_x4(a[4], a[5], a[6], a[7], sb + OFF_QM + o1);
                float sc[4] = {0.f, 0.f, 0.f, 0.f}, sc1[4] = {0.f, 0.f, 0.f, 0.f};
                mma16816(sc, a[0], 0, a[1], 0, b[0], b[1]);
                mma16816(sc1, a[2], 0, a[3], 0, b[2], b[3]);
                bar_arrive(NB_QK2, 384);
                mma16816(sc, a[4], 0, a[5], 0, b[4], b[5]);
                mma16816(sc1, a[6], 0, a[7], 0, b[6], b[7]);
                const float s0 = sc[0] + sc1[0], s1 = sc[1] + sc1[1];
                const uint32_t dst = sb + OFF_S + (vrank() * 5) * 256 + lane * 8;
#pragma unroll
                for (uint32_t r = 0; r < 3; r++) st_async_v2f(mapa(dst, r), s0, s1, mapa(bars + BAR_S, r));
            } else {
                bar_arrive(NB_QK2, 384);
            }
            {
                const int tt = vtid(), lane = tt & 31, warp = (tt >> 5) & 3;
                mbar_wait(bars + BAR_S, s & 1);
                float sv[10];
#pragma unroll
                for (int j = 0; j < 5; j++) {
                    const float2 p0 = lds64f(sb + OFF_S + (0 * 5 + j) * 256 + lane * 8);
                    const float2 p1 = lds64f(sb + OFF_S + (1 * 5 + j) * 256 + lane * 8);
                    const float2 p2 = lds64f(sb + OFF_S + (2 * 5 + j) * 256 + lane * 8);
                    sv[2 * j] = p0.x + p1.x + p2.x;
                    sv[2 * j + 1] = p0.y + p1.y + p2.y;
                }
                float mx = fmaxf(fmaxf(fmaxf(sv[0], sv[1]), fmaxf(sv[2], sv[3])),
                                 fmaxf(fmaxf(fmaxf(sv[4], sv[5]), fmaxf(sv[6], sv[7])), fmaxf(sv[8], sv[9])));
                mx = fmaxf(mx, __shfl_xor_sync(0xffffffffu, mx, 1));
                mx = fmaxf(mx, __shfl_xor_sync(0xffffffffu, mx, 2));
                const float sl2 = 0.07216878364870322f * 1.4426950408889634f;
#pragma unroll
                for (int j = 0; j < 10; j++) sv[j] = ex2((sv[j] - mx) * sl2);
                uint32_t p[5];
#pragma unroll
                for (int j = 0; j < 5; j++) p[j] = pack_bf16(sv[2 * j], sv[2 * j + 1]);
                float rs[4] = {0.f, 0.f, 0.f, 0.f};
                mma16816(rs, p[0], 0, p[1], 0, 0x3F803F80u, 0x3F803F80u);
                mma16816(rs, p[2], 0, p[3], 0, 0x3F803F80u, 0x3F803F80u);
                mma16816(rs, p[4], 0, 0, 0, 0x3F803F80u, 0);
                bar_sync(NB_V, 384);
                float o0[4] = {0.f, 0.f, 0.f, 0.f}, o1[4] = {0.f, 0.f, 0.f, 0.f};
                const int mid = lane >> 3, i = lane & 7;
                const uint32_t vb = sb + OFF_V + ((mid & 1) * 8 + i) * 128 + (((2 * warp + (mid >> 1)) ^ i) << 4);
                uint32_t b0, b1, b2, b3, b4, b5, b6, b7, b8, b9;
                ldsm_x4_t(b0, b1, b2, b3, vb);
                ldsm_x4_t(b4, b5, b6, b7, vb + 2048);
                ldsm_x2_t(b8, b9, sb + OFF_V + (32 + i) * 128 + (((2 * warp + (mid & 1)) ^ i) << 4));
                mma16816(o0, p[0], 0, p[1], 0, b0, b1);
                mma16816(o1, p[0], 0, p[1], 0, b2, b3);
                mma16816(o0, p[2], 0, p[3], 0, b4, b5);
                mma16816(o1, p[2], 0, p[3], 0, b6, b7);
                mma16816(o0, p[4], 0, 0, 0, b8, 0);
                mma16816(o1, p[4], 0, 0, 0, b9, 0);
                const float inv = rcpf(rs[0]);
                const uint32_t w0 = pack_bf16(o0[0] * inv, o0[1] * inv), w1 = pack_bf16(o1[0] * inv, o1[1] * inv);
                const uint32_t rk = vrank();
                const uint32_t oc = sb + OFF_O + rk * 1024;
                asm volatile("stmatrix.sync.aligned.m8n8.x2.shared.b16 [%0], {%1,%2};"
                             ::"r"(oc + i * 128 + (((2 * warp + (mid & 1)) ^ i) << 4)), "r"(w0), "r"(w1) : "memory");
                fence_proxy_async();
                bar_sync(NB_WG1, 128);
                if (lane == 0) {
                    if (warp == 0) bulk_to_peer(oc, bars + BAR_O, rk == 0 ? 1 : 0);
                    else if (warp == 1) bulk_to_peer(oc, bars + BAR_O, rk == 2 ? 1 : 2);
                    else if (warp == 2) mbar_arrive(bars + BAR_OL);
                }
            }
            {
                float acc[4];
                if (s == 0) mbar_wait(bars + BAR_W3, 0);
                uint32_t* pp = partial_ptr(s % 3, (int)vrank() * 24 + 8, 1, vhead());
                wo_tile_mixed3(acc, WO, sb + OFF_WO + WO_B, sb + OFF_O, bars + BAR_OL, bars + BAR_O, s & 1);
                store_partial(acc, pp, 1);
            }
            bar_sync(NB_WO, 384);
            copy_rows_out<8>(sb + OFF_K, g_Km + (size_t)s * NMEM * HD + (vcta() * 64));
            {
                float d[16];
                mbar_wait(bars + BAR_X, (s + 1) & 1);
                x_part_rs(d, W, sb + OFF_X);
                store_xT(sb + OFF_K + 1024, d);
                fence_proxy_async();
                bar_arrive(NB_KX, 256);
            }
            if ((vtid() & 127) == 96) {
                fence_gpu();
                if (s > 0) atomicAdd(&g_cflag[(s - 1) * 8 + (vhead() >> 2)], 1u);
            }
            __syncwarp();

        }
    } else {
        reg_dec<64>();
        bar_sync(NB_MEM, 384);
        asm volatile("barrier.cluster.arrive.release.aligned; barrier.cluster.wait.acquire.aligned;" ::: "memory");
        issue_x_load(sb, &tmX, 0);
        if ((tid & 127) == 96) {
            mbar_expect_tx(bars + BAR_W2, 81920);
            for (int i = 0; i < 5; i++) tma_load_2d(sb + OFF_WV + i * 16384, &tmWv, c0, i * 128, bars + BAR_W2);
            mbar_expect_tx(bars + BAR_W3, 24576 + 18432 + 24576 + 8192);
            tma_load_2d(sb + OFF_WO + WO_A, &tmWo, (tb + 0) * 64, h * DH, bars + BAR_W3);
            tma_load_2d(sb + OFF_WO + WO_A + 12288, &tmWo, (tb + 0) * 64, h * DH + 96, bars + BAR_W3);
            tma_load_2d(sb + OFF_WO + WO_B, &tmWo, (tb + 1) * 64, h * DH + 48, bars + BAR_W3);
            for (int i = 0; i < 3; i++)
                tma_load_2d(sb + OFF_WO + WO_B + 12288 + i * 2048, &tmWo16, (tb + 1) * 64, h * DH + 144 + 16 * i, bars + BAR_W3);
            tma_load_2d(sb + OFF_WO + WO_C, &tmWo, (tb + 2) * 64, h * DH, bars + BAR_W3);
            tma_load_2d(sb + OFF_WO + WO_C + 12288, &tmWo, (tb + 2) * 64, h * DH + 96, bars + BAR_W3);
            for (int i = 0; i < 4; i++)
                tma_load_2d(sb + OFF_WO + WO_E + i * 2048, &tmWo16, 576, c0 + 16 * i, bars + BAR_W3);
        }
        {
            const int t = tid & 127;
#pragma unroll
            for (int i = 0; i < 5; i++) {
                const int v = i * 128 + t, cg = v >> 3, tok = v & 7;
                const uint4 val = *reinterpret_cast<const uint4*>(mem0 + tok * DM + cg * 8);
                sts128(sb + OFF_MEM + cg * 128 + tok * 16, val);
            }
        }
        fence_proxy_async();
        mbar_wait(bars + BAR_W2, 0);
        if ((tid & 127) == 0) atomicAdd(&g_wflag, 1u);
        bar_sync(NB_WG2, 128);
        if ((tid & 127) < 3) {
            const int i = tid & 127, cnt = i == (int)rank ? (rank == 0 ? 4 : 3) : 1;
            for (int q = 0; q < cnt; q++) mbar_arrive(bars + BAR_C + i * 8);
        }
#pragma unroll 1
        for (int s = 0; s < NSEG; s++) {
            if (s < NSEG - 1) {
                const int t = vtid() & 127;
                if (t == 0) mbar_expect_tx(bars + BAR_S, 3840);
                if (t == 32) mbar_expect_tx(bars + BAR_O, 2048);
            }
            bar_sync(NB_QK2, 384);
            {
                float acc[4] = {0.f, 0.f, 0.f, 0.f};
                wg_fence();
                static_for<0, 40>([&](auto I) {
                    constexpr int ks = decltype(I)::value;
                    wgmma_ss_n8_ta_bns<((ks * 2048) >> 4), ((ks * 256) >> 4)>(acc, desc_lo(sb + OFF_WV), (((sb + OFF_MEM) & 0x3FFFF) >> 4) | (8u << 16));
                });
                wg_commit();
                wg_wait<0>();
                store_memT(sb + OFF_V, acc);
            }
            if (s < NSEG - 1) {
                bar_arrive(NB_V, 384);
                {
                    const int t = vtid() & 127;
                    if (t >= 64 && t < 67 && (uint32_t)(t - 64) != vrank()) mbar_expect_tx(bars + BAR_C + (t - 64) * 8, t == 64 ? 4096 : 3072);
                }
                mbar_wait(bars + BAR_S, s & 1);
                issue_x_load(sb, &tmX, s + 1);
            }
            bar_sync(NB_WG2, 128);
            copy_rows_out<8>(sb + OFF_V, g_Vm + (size_t)s * NMEM * HD + vcta() * 64);
            if (s == NSEG - 1) { bar_arrive(NB_OUT, 384); break; }
            const int vb = vcta(), vh = vb / 3, vr = vb - 3 * vh;
            {
                if (s == 0) mbar_wait(bars + BAR_W3, 0);
                uint32_t* pp = partial_ptr(s % 3, 72 + vr, 3, vh);
                mbar_wait(bars + BAR_OL, s & 1);
                float acc[4] = {0.f, 0.f, 0.f, 0.f};
                wg_fence();
                static_for<0, 4>([&](auto I) {
                    constexpr int ks = decltype(I)::value;
                    wgmma_ss_n8_ta<((ks * 2048) >> 4), ((ks * 32) >> 4)>(acc, desc_lo(sb + OFF_WO + WO_E), desc_lo(sb + OFF_O + vr * 1024));
                });
                wg_commit();
                wg_wait<0>();
                store_partial(acc, pp, 3);
            }
            {
                float acc[4];
                uint32_t* pp = partial_ptr(s % 3, (3 * vr + 2) * 8, 1, vh);
                wo_tile_ss(acc, sb + OFF_WO + WO_C, sb + OFF_O, bars + BAR_OL, bars + BAR_O, s & 1);
                store_partial(acc, pp, 1);
            }
            bar_arrive(NB_WO, 384);
            spin_cycles(DELAY_A);
            reduce_partials(s, sb + OFF_S);
            spin_cycles(DELAY_B);
            gather_memory(s, sb, vrank());
        }
    }
}

}

namespace cbig {
#define POLL_LIMIT (1u << 18)
namespace ch {
constexpr int OFF_WV = 0;
constexpr int OFF_WO = 81920;
constexpr int WO_A = 0, WO_B = 18432, WO_C = 36864, WO_E = 61440;
constexpr int OFF_R1 = 151552;
constexpr int OFF_RE = 154880;
constexpr int OFF_X = 163840;
constexpr int OFF_MEM = 204800;
constexpr int OFF_K = 215040;
constexpr int OFF_V = 220160;
constexpr int OFF_S = 225280;
constexpr int OFF_BAR = OFF_S + 3840;
constexpr int OFF_O = 229376;
constexpr int OFF_QM = 157696;
constexpr int OFF_Q = 158720;
constexpr int SMEM_BYTES = OFF_O + 3072;
constexpr int BAR_W1 = 0, BAR_W2 = 8, BAR_X = 16, BAR_S = 24, BAR_O = 32, BAR_W3 = 40, BAR_OL = 48, BAR_C = 56, BAR_R1 = 64, BAR_RE = 72;
constexpr int NB_MEM = 1, NB_QK = 2, NB_OUT = 3, NB_WG1 = 4, NB_WG2 = 5, NB_V = 6, NB_QK2 = 7, NB_KX = 8, NB_WO = 9, NB_WG0 = 10;
}

DEVINL uint32_t vq() { uint32_t r; asm("mov.u32 %0, %%cluster_ctarank;" : "=r"(r)); return r; }
DEVINL int vcl() { int t; asm("mov.u32 %0, %%clusterid.x;" : "=r"(t)); return t; }
DEVINL int vnh() { return vcl() < 4 ? 5 : 4; }
DEVINL uint32_t vrank() { return vq() % 3; }
DEVINL uint32_t vq0() { const uint32_t q = vq(); return q - q % 3; }
DEVINL int vhead() { const int c = vcl(); return (c < 4 ? 5 * c : 4 * c + 4) + (int)(vq() / 3); }
DEVINL int vcta() { return vhead() * 3 + (int)vrank(); }
DEVINL int vtid() { int t; asm volatile("mov.u32 %0, %%tid.x;" : "=r"(t)); return t; }

template <int NKS>
DEVINL void load_afrags(uint32_t (&W)[NKS][4], uint32_t tile, int warp, int lane) {
    const int mid = lane >> 3, i = lane & 7;
    const uint32_t base = tile + ((mid >> 1) * 8 + i) * 128 + (((2 * warp + (mid & 1)) ^ i) << 4);
#pragma unroll
    for (int ks = 0; ks < NKS; ks++) ldsm_x4_t(W[ks][0], W[ks][1], W[ks][2], W[ks][3], base + ks * 2048);
}

DEVINL void mem_part_regs(float (&acc)[4], const uint32_t (&W)[40][4], uint32_t sXM, uint32_t barC, uint32_t par) {
    const int lane = vtid() & 31;
    float c1[4] = {0.f, 0.f, 0.f, 0.f}, c2[4] = {0.f, 0.f, 0.f, 0.f}, c3[4] = {0.f, 0.f, 0.f, 0.f};
    acc[0] = acc[1] = acc[2] = acc[3] = 0.f;
    const int mid = lane >> 3, tok = lane & 7;
    const uint32_t a0 = sXM + mid * 128 + tok * 16;
    const uint32_t a1 = a0 + 512;
    uint32_t b[2][8];
    constexpr int order[10] = {0, 1, 2, 3, 4, 5, 6, 7, 8, 9};
    mbar_wait(barC, par);
    ldsm_x4(b[0][0], b[0][1], b[0][2], b[0][3], a0);
    ldsm_x4(b[0][4], b[0][5], b[0][6], b[0][7], a1);
#pragma unroll
    for (int n = 0; n < 10; n++) {
        const int c = order[n];
        if (n < 9) {
            const int cn = order[n + 1];
            ldsm_x4(b[(n + 1) & 1][0], b[(n + 1) & 1][1], b[(n + 1) & 1][2], b[(n + 1) & 1][3], a0 + cn * 1024);
            ldsm_x4(b[(n + 1) & 1][4], b[(n + 1) & 1][5], b[(n + 1) & 1][6], b[(n + 1) & 1][7], a1 + cn * 1024);
        }
        mma16816(acc, W[4 * c][0], W[4 * c][1], W[4 * c][2], W[4 * c][3], b[n & 1][0], b[n & 1][1]);
        mma16816(c1, W[4 * c + 1][0], W[4 * c + 1][1], W[4 * c + 1][2], W[4 * c + 1][3], b[n & 1][2], b[n & 1][3]);
        mma16816(c2, W[4 * c + 2][0], W[4 * c + 2][1], W[4 * c + 2][2], W[4 * c + 2][3], b[n & 1][4], b[n & 1][5]);
        mma16816(c3, W[4 * c + 3][0], W[4 * c + 3][1], W[4 * c + 3][2], W[4 * c + 3][3], b[n & 1][6], b[n & 1][7]);
    }
#pragma unroll
    for (int i = 0; i < 4; i++) acc[i] = (acc[i] + c1[i]) + (c2[i] + c3[i]);
}

DEVINL void store_memT(uint32_t rows, const float (&acc)[4]) {
    const int tt = vtid(), warp = (tt >> 5) & 3, lane = tt & 31;
    const uint32_t r0 = pack_bf16(acc[0], acc[1]), r1 = pack_bf16(acc[2], acc[3]);
    const int i = lane & 7, half = (lane >> 3) & 1;
    stsm_x2_t(rows + i * 128 + (((2 * warp + half) ^ i) << 4), r0, r1);
}

DEVINL void store_xT(uint32_t rows, const float (&d)[16]) {
    const int tt = vtid(), warp = (tt >> 5) & 3, lane = tt & 31;
    const int i = lane & 7, mid = lane >> 3;
    const int half = mid & 1, jj = mid >> 1;
    const uint32_t base = rows + (jj * 8 + i) * 128 + (((2 * warp + half) ^ i) << 4);
#pragma unroll
    for (int q = 0; q < 2; q++) {
        const int j0 = 2 * q, j1 = 2 * q + 1;
        const uint32_t r0 = pack_bf16(d[4 * j0 + 0], d[4 * j0 + 1]);
        const uint32_t r1 = pack_bf16(d[4 * j0 + 2], d[4 * j0 + 3]);
        const uint32_t r2 = pack_bf16(d[4 * j1 + 0], d[4 * j1 + 1]);
        const uint32_t r3 = pack_bf16(d[4 * j1 + 2], d[4 * j1 + 3]);
        stsm_x4_t(base + q * 2048, r0, r1, r2, r3);
    }
}

template <int NROWS>
DEVINL void copy_rows_out(uint32_t rows, bf16* gdst) {
    const int t = vtid() & 127;
    const int row = t >> 3, slot = t & 7;
    const uint32_t src = rows + row * 128 + ((slot ^ (row & 7)) << 4);
    bf16* dst = gdst + row * HD + slot * 8;
#pragma unroll
    for (int it = 0; it < (NROWS + 15) / 16; it++) {
        if (NROWS >= 16 * (it + 1) || row + 16 * it < NROWS) stg128(dst + it * 16 * HD, lds128(src + it * 2048));
    }
}

struct PartialDst { uint32_t a0, a1, rk; };
DEVINL uint32_t uni(uint32_t v) { return __shfl_sync(0xffffffffu, v, 0); }
DEVINL PartialDst partial_dst(uint32_t sb, int u0) {
    const int warp = (threadIdx.x >> 5) & 3;
    const int nh = vnh(), per = nh == 5 ? 5 : 6, j = (int)(vq() / 3), r = (int)vrank();
    PartialDst d;
    const int ua = u0 + 2 * warp, ub = ua + 1;
    const int ja = ua / per, jb = ub / per;
    d.a0 = uni(mapa(sb + ch::OFF_R1 + ((ua - ja * per) * nh + j) * 128, 3 * ja + r));
    d.a1 = uni(mapa(sb + ch::OFF_R1 + ((ub - jb * per) * nh + j) * 128, 3 * jb + r));
    d.rk = uni((uint32_t)(3 * ja + r) | ((uint32_t)(3 * jb + r) << 8));
    return d;
}
DEVINL PartialDst partial_dst_e(uint32_t sb) {
    const int warp = (threadIdx.x >> 5) & 3;
    const uint32_t a = sb + ch::OFF_RE + vq() * 128;
    PartialDst d;
    d.a0 = uni(mapa(a, 2 * warp));
    d.a1 = uni(mapa(a, 2 * warp + 1));
    d.rk = uni((uint32_t)(2 * warp) | ((uint32_t)(2 * warp + 1) << 8));
    return d;
}
DEVINL void st_async_b32(uint32_t addr, uint32_t v, uint32_t bar) {
    asm volatile("st.async.weak.shared::cluster.mbarrier::complete_tx::bytes.b32 [%0], %1, [%2];" ::"r"(addr), "r"(v), "r"(bar) : "memory");
}
DEVINL void store_partial(const float (&acc)[4], const PartialDst& d, uint32_t bar) {
    const uint32_t l4 = (vtid() & 31) * 4;
    st_async_b32(d.a0 + l4, pack_bf16(acc[0], acc[1]), mapa(bar, d.rk & 255u));
    st_async_b32(d.a1 + l4, pack_bf16(acc[2], acc[3]), mapa(bar, d.rk >> 8));
}

DEVINL void x_part_rs(float (&d)[16], const uint32_t (&W)[40][4], uint32_t sXM) {
#pragma unroll
    for (int i = 0; i < 16; i++) d[i] = 0.f;
    const uint32_t blo = desc_lo(sXM);
    wg_fence();
    static_for<0, 40>([&](auto I) {
        constexpr int ks = decltype(I)::value;
        wgmma_rs_n32<(((ks >> 2) * 4096 + (ks & 3) * 32) >> 4)>(d, W[ks], blo);
    });
    wg_commit();
    wg_wait<0>();
}

DEVINL void x_part_ss(float (&d)[16], uint32_t sW, uint32_t sXM) {
#pragma unroll
    for (int i = 0; i < 16; i++) d[i] = 0.f;
    const uint32_t alo = desc_lo(sW), blo = desc_lo(sXM);
#pragma unroll 1
    for (int p = 0; p < 40 / VX_GROUP; p++) {
        wg_fence();
        static_for<0, VX_GROUP>([&](auto I) {
            constexpr int ks = decltype(I)::value;
            wgmma_ss_n32_ta<((ks * 2048) >> 4), (((ks >> 2) * 4096 + (ks & 3) * 32) >> 4)>(d, alo + p * (VX_GROUP * 128), blo + p * (VX_GROUP / 4 * 256));
        });
        wg_commit();
        wg_wait<0>();
    }
}

DEVINL void wo_chunk_ss(float (&acc)[4], uint32_t alo, uint32_t blo, uint32_t q) {
    const uint32_t a = alo + q * 512, b = blo + q * 64;
    wgmma_ss_n8_ta<0, 0>(acc, a, b);
    wgmma_ss_n8_ta<128, 2>(acc, a, b);
    wgmma_ss_n8_ta<256, 4>(acc, a, b);
    wgmma_ss_n8_ta<384, 6>(acc, a, b);
}
DEVINL void wo_tile_ss(float (&acc)[4], uint32_t tile, uint32_t sO, uint32_t barOL, uint32_t barO, uint32_t par) {
    const uint32_t rk = vrank(), alo = desc_lo(tile), blo = desc_lo(sO);
    acc[0] = acc[1] = acc[2] = acc[3] = 0.f;
    mbar_wait(barOL, par);
    wg_fence();
    wo_chunk_ss(acc, alo, blo, rk);
    wg_commit();
    mbar_wait(barO, par);
    wg_fence();
    wo_chunk_ss(acc, alo, blo, rk == 0 ? 1 : 0);
    wo_chunk_ss(acc, alo, blo, rk == 2 ? 1 : 2);
    wg_commit();
    wg_wait<0>();
}

DEVINL void wo_chunk_mixed3(float (&acc)[4], const uint32_t (&WO)[3][4], uint32_t hlo, uint32_t blo, uint32_t q) {
    if (q == 0) {
        wgmma_ss_n8_ta<0, 6>(acc, hlo, blo);
        wgmma_rs_n8<0>(acc, WO[0], blo);
        wgmma_rs_n8<2>(acc, WO[1], blo);
        wgmma_rs_n8<4>(acc, WO[2], blo);
    } else {
        wo_chunk_ss(acc, hlo - 384, blo, q);
    }
}
DEVINL void wo_tile_mixed3(float (&acc)[4], const uint32_t (&WO)[3][4], uint32_t hi, uint32_t sO, uint32_t barOL, uint32_t barO, uint32_t par) {
    const uint32_t rk = vrank(), hlo = desc_lo(hi), blo = desc_lo(sO);
    acc[0] = acc[1] = acc[2] = acc[3] = 0.f;
    mbar_wait(barOL, par);
    wg_fence();
    wo_chunk_mixed3(acc, WO, hlo, blo, rk);
    wg_commit();
    mbar_wait(barO, par);
    wg_fence();
    wo_chunk_mixed3(acc, WO, hlo, blo, rk == 0 ? 1 : 0);
    wo_chunk_mixed3(acc, WO, hlo, blo, rk == 2 ? 1 : 2);
    wg_commit();
    wg_wait<0>();
}

DEVINL void issue_x_load(uint32_t sb, const CUtensorMap* tmX, int seg) {
    const int tt = vtid(), warp = (tt >> 5) & 3;
    if ((tt & 31) == 0) {
        if (warp == 0) mbar_expect_tx(sb + ch::OFF_BAR + ch::BAR_X, 40960);
        const int i = (int)vrank() + 3 * warp;
        if (i < 10)
            asm volatile(
                "cp.async.bulk.tensor.2d.shared::cluster.global.mbarrier::complete_tx::bytes.multicast::cluster [%0], [%1, {%3, %4}], [%2], %5;"
                ::"r"(sb + ch::OFF_X + i * 4096), "l"(tmX), "r"(sb + ch::OFF_BAR + ch::BAR_X), "r"(i * 64), "r"(seg * SEG), "h"((uint16_t)(7u << vq0())) : "memory");
    }
}

DEVINL void store_tile_tma(uint32_t src, const CUtensorMap* m, int c0, int seg) {
    asm volatile("cp.async.bulk.tensor.2d.global.shared::cta.bulk_group [%0, {%2, %3}], [%1];" ::"l"(m), "r"(src), "r"(c0), "r"(seg * SEG) : "memory");
}
DEVINL void bulk_commit() { asm volatile("cp.async.bulk.commit_group;" ::: "memory"); }

DEVINL void recycle_slots(int s) {
    const int t = vtid() & 127, w = t >> 5, lane = t & 31;
    const int nh = vnh(), per = nh == 5 ? 5 : 6, j = (int)(vq() / 3), r = (int)vrank(), c = vcl();
    uint32_t* base = g_P2 + (((s + 3) & 3) * 80 * 7 + c) * 32 + lane;
    for (int ul = w; ul < per; ul += 4) {
        const int u = j * per + ul;
        if (u < 24) st_relaxed_u32(base + (r * 24 + u) * 7 * 32, 0u);
    }
    if (w == 3 && vq() < 8) st_relaxed_u32(base + (72 + (int)vq()) * 7 * 32, 0u);
}

#define DELAY_G 150
DEVINL void spin_cycles(uint32_t n) {
    uint32_t t0, t1;
    asm volatile("mov.u32 %0, %%clock;" : "=r"(t0));
    do { asm volatile("mov.u32 %0, %%clock;" : "=r"(t1)); } while (t1 - t0 < n);
}
DEVINL float bf_lo(uint32_t w) { return __uint_as_float(w << 16); }
DEVINL float bf_hi(uint32_t w) { return __uint_as_float(w & 0xffff0000u); }
DEVINL uint32_t ld_relaxed_u32(const void* p) {
    uint32_t v;
    asm volatile("ld.relaxed.gpu.global.u32 %0, [%1];" : "=r"(v) : "l"(p) : "memory");
    return v;
}

DEVINL uint32_t lds32(uint32_t a) { uint32_t v; asm volatile("ld.shared.u32 %0, [%1];" : "=r"(v) : "r"(a) : "memory"); return v; }

DEVINL void reduce_cluster(int s, uint32_t sb) {
    const int tt = vtid(), lane = tt & 31, warp = (tt >> 5) & 3;
    const int nh = vnh(), per = nh == 5 ? 5 : 6, j = (int)(vq() / 3), r = (int)vrank(), c = vcl();
    uint32_t* base = g_P2 + (((s + 1) & 3) * 80 * 7 + c) * 32 + lane;
    if (warp == 3 && vq() < 8) {
        mbar_wait(sb + ch::OFF_BAR + ch::BAR_RE, s & 1);
        uint32_t v[15];
#pragma unroll
        for (int q = 0; q < 15; q++) v[q] = q < 3 * nh ? lds32(sb + ch::OFF_RE + q * 128 + lane * 4) : 0u;
        float lo = 0.f, hi = 0.f, lo2 = 0.f, hi2 = 0.f;
#pragma unroll
        for (int q = 0; q < 14; q += 2) { lo += bf_lo(v[q]); hi += bf_hi(v[q]); lo2 += bf_lo(v[q + 1]); hi2 += bf_hi(v[q + 1]); }
        const uint32_t word = pack_bf16((lo + bf_lo(v[14])) + lo2, (hi + bf_hi(v[14])) + hi2);
        st_relaxed_u32(base + (72 + (int)vq()) * 7 * 32, word ? word : 0x00008000u);
    }
    mbar_wait(sb + ch::OFF_BAR + ch::BAR_R1, s & 1);
    const int first = warp < 3 ? warp : 99, step3 = 3;
    (void)step3;
    if (warp < 3) {
#pragma unroll
        for (int k = 0; k < 2; k++) {
            const int ul = first + 3 * k, u = j * per + ul;
            if (ul < per && u < 24) {
                uint32_t v[5];
#pragma unroll
                for (int q = 0; q < 5; q++) v[q] = q < nh ? lds32(sb + ch::OFF_R1 + (ul * nh + q) * 128 + lane * 4) : 0u;
                const float lo = ((bf_lo(v[0]) + bf_lo(v[1])) + (bf_lo(v[2]) + bf_lo(v[3]))) + bf_lo(v[4]);
                const float hi = ((bf_hi(v[0]) + bf_hi(v[1])) + (bf_hi(v[2]) + bf_hi(v[3]))) + bf_hi(v[4]);
                const uint32_t word = pack_bf16(lo, hi);
                st_relaxed_u32(base + (r * 24 + u) * 7 * 32, word ? word : 0x00008000u);
            }
        }
    }
}

DEVINL void bulk_to_peer(uint32_t src, uint32_t bytes, uint32_t bar, uint32_t r) {
    asm volatile("cp.async.bulk.shared::cluster.shared::cta.mbarrier::complete_tx::bytes [%0], [%1], %3, [%2];"
                 ::"r"(mapa(src, r)), "r"(src), "r"(mapa(bar, r)), "r"(bytes) : "memory");
}

DEVINL void gather_memory(int s, uint32_t sb, long long* dbg) {
    const int tt = vtid(), lane = tt & 31, warp = (tt >> 5) & 3;
    const int nact = 3 * vnh(), q = (int)vq();
    const int big = nact == 15 ? 5 : 8, sz = nact == 15 ? 5 : 6;
    const int n = q < big ? sz + 1 : sz, start = q < big ? q * (sz + 1) : big * (sz + 1) + (q - big) * sz;
    const uint32_t* base = g_P2 + ((s + 1) & 3) * 80 * 7 * 32 + lane;
    const bool two = warp + 4 < n;
    const uint32_t* s0 = base + (start + warp) * 7 * 32;
    const uint32_t* s1 = s0 + 4 * 7 * 32;
    uint32_t v[7], w[7];
#pragma unroll
    for (int i = 0; i < 7; i++) v[i] = ld_relaxed_u32(s0 + i * 32);
#pragma unroll
    for (int i = 0; i < 7; i++) w[i] = two ? ld_relaxed_u32(s1 + i * 32) : 1u;
    uint32_t cnt = 0;
    while (true) {
        bool ok = true;
#pragma unroll
        for (int i = 0; i < 7; i++) {
            if (v[i] == 0) { v[i] = ld_relaxed_u32(s0 + i * 32); ok = false; }
            if (w[i] == 0) { w[i] = ld_relaxed_u32(s1 + i * 32); ok = false; }
        }
        if (ok) break;
        if (++cnt > POLL_LIMIT) break;
    }
    __syncwarp();
    {
        const float lo = ((bf_lo(v[0]) + bf_lo(v[1])) + (bf_lo(v[2]) + bf_lo(v[3]))) + ((bf_lo(v[4]) + bf_lo(v[5])) + bf_lo(v[6]));
        const float hi = ((bf_hi(v[0]) + bf_hi(v[1])) + (bf_hi(v[2]) + bf_hi(v[3]))) + ((bf_hi(v[4]) + bf_hi(v[5])) + bf_hi(v[6]));
        uint32_t word = pack_bf16(lo, hi);
        asm volatile("movmatrix.sync.aligned.m8n8.trans.b16 %0, %0;" : "+r"(word));
        asm volatile("st.shared.u32 [%0], %1;" ::"r"(sb + ch::OFF_MEM + (start + warp) * 128 + lane * 4), "r"(word) : "memory");
    }
    if (two) {
        const float lo = ((bf_lo(w[0]) + bf_lo(w[1])) + (bf_lo(w[2]) + bf_lo(w[3]))) + ((bf_lo(w[4]) + bf_lo(w[5])) + bf_lo(w[6]));
        const float hi = ((bf_hi(w[0]) + bf_hi(w[1])) + (bf_hi(w[2]) + bf_hi(w[3]))) + ((bf_hi(w[4]) + bf_hi(w[5])) + bf_hi(w[6]));
        uint32_t word = pack_bf16(lo, hi);
        asm volatile("movmatrix.sync.aligned.m8n8.trans.b16 %0, %0;" : "+r"(word));
        asm volatile("st.shared.u32 [%0], %1;" ::"r"(sb + ch::OFF_MEM + (start + warp + 4) * 128 + lane * 4), "r"(word) : "memory");
    }
    fence_proxy_async();
    bar_sync(ch::NB_WG2, 128);
    const uint32_t bar = sb + ch::OFF_BAR + ch::BAR_C, src = sb + ch::OFF_MEM + start * 128;
    const int d = 4 * lane + warp;
    if (lane < 4 && d < nact && d != q) bulk_to_peer(src, n * 128, bar, d);
    if (tt == 256) mbar_expect_tx(bar, 10240 - n * 128);
}

__global__ void __launch_bounds__(384, 1)
chain_big_kernel(const __grid_constant__ CUtensorMap tmWq, const __grid_constant__ CUtensorMap tmWk,
             const __grid_constant__ CUtensorMap tmWv, const __grid_constant__ CUtensorMap tmWo,
             const __grid_constant__ CUtensorMap tmWo16, const __grid_constant__ CUtensorMap tmX,
             const __grid_constant__ CUtensorMap tmQo, const __grid_constant__ CUtensorMap tmKo, const __grid_constant__ CUtensorMap tmVo,
             const bf16* __restrict__ mem0, long long* __restrict__ dbg) {
    using namespace ch;
    extern __shared__ __align__(1024) uint8_t smem_raw[];
    const uint32_t sb = smem_u32(smem_raw);
    const int tid = threadIdx.x, wg = tid >> 7;
    asm volatile("griddepcontrol.launch_dependents;" ::: "memory");
    if ((int)(vq() / 3) >= vnh()) return;
    const uint32_t rank = vrank();
    const int h = vhead();
    const int c0 = h * DH + 64 * (int)rank;
    const int tb = 3 * (int)rank;
    const uint32_t bars = sb + OFF_BAR;

    if (tid == 0) {
        mbar_init(bars + BAR_W1, 3);
        mbar_init(bars + BAR_W2, 1);
        mbar_init(bars + BAR_W3, 1);
        mbar_init(bars + BAR_X, 1);
        mbar_init(bars + BAR_S, 1);
        mbar_init(bars + BAR_O, 1);
        mbar_init(bars + BAR_OL, 1);
        mbar_init(bars + BAR_C, 1);
        mbar_init(bars + BAR_R1, 1);
        mbar_init(bars + BAR_RE, 1);
        asm volatile("fence.mbarrier_init.release.cluster;" ::: "memory");
    }
    if ((tid & 31) == 0) {
        const CUtensorMap* m = tid == 0 ? &tmWq : tid == 32 ? &tmWo16 : tid == 64 ? &tmX : tid == 96 ? &tmQo : tid == 128 ? &tmWk
                             : tid == 160 ? &tmWo : tid == 192 ? &tmKo : tid == 224 ? &tmVo : &tmWv;
        asm volatile("prefetch.tensormap [%0];" ::"l"(m) : "memory");
    }
    __syncthreads();
    if (tid == 0) {
        mbar_expect_tx(bars + BAR_W1, 81920);
        for (int i = 0; i < 5; i++) tma_load_2d(sb + OFF_WV + i * 16384, &tmWq, c0, i * 128, bars + BAR_W1);
    } else if (tid == 128) {
        mbar_expect_tx(bars + BAR_W1, 81920);
        for (int i = 0; i < 5; i++) tma_load_2d(sb + OFF_WO + i * 16384, &tmWk, c0, i * 128, bars + BAR_W1);
    } else if (tid == 256) {
        mbar_expect_tx(bars + BAR_W1, 2 * 12288);
        tma_load_2d(sb + OFF_X, &tmWo, (tb + 0) * 64, h * DH, bars + BAR_W1);
        tma_load_2d(sb + OFF_X + 12288, &tmWo, (tb + 1) * 64, h * DH, bars + BAR_W1);
        for (int i = 0; i < 5; i++) tma_prefetch_2d(&tmWv, c0, i * 128);
    }

    if (wg == 0) {
        reg_inc<224>();
        uint32_t W[40][4], WO[3][4];
        mbar_wait(bars + BAR_W1, 0);
        load_afrags<40>(W, sb + OFF_WV, (tid >> 5) & 3, tid & 31);
        load_afrags<3>(WO, sb + OFF_X, (tid >> 5) & 3, tid & 31);
        bar_sync(NB_MEM, 384);
        asm volatile("barrier.cluster.arrive.release.aligned; barrier.cluster.wait.acquire.aligned;" ::: "memory");
        {
            float d[16];
            mbar_wait(bars + BAR_X, 0);
            x_part_rs(d, W, sb + OFF_X);
            store_xT(sb + OFF_Q, d);
            mbar_wait(bars + BAR_W2, 0);
            x_part_ss(d, sb + OFF_WV, sb + OFF_X);
            store_xT(sb + OFF_V + 1024, d);
            fence_proxy_async();
            bar_arrive(NB_V, 384);
        }
        const PartialDst pdA = partial_dst(sb, 0);
#pragma unroll 1
        for (int s = 0; s < NSEG - 1; s++) {
            {
                float acc[4];
                mem_part_regs(acc, W, sb + OFF_MEM, bars + BAR_C, s & 1);
                store_memT(sb + OFF_QM, acc);
            }
            bar_arrive(NB_QK, 256);
            bar_sync(NB_KX, 256);
            {
                const int tt = vtid(), lane = tt & 31, j = ((tt >> 5) & 3) + 1;
                const int mid = lane >> 3, i = lane & 7;
                const uint32_t o0 = i * 128 + ((mid ^ i) << 4), o1 = o0 ^ 64;
                uint32_t a[8], b[8];
                ldsm_x4(b[0], b[1], b[2], b[3], sb + OFF_K + j * 1024 + o0);
                ldsm_x4(b[4], b[5], b[6], b[7], sb + OFF_K + j * 1024 + o1);
                ldsm_x4(a[0], a[1], a[2], a[3], sb + OFF_QM + o0);
                ldsm_x4(a[4], a[5], a[6], a[7], sb + OFF_QM + o1);
                float sc[4] = {0.f, 0.f, 0.f, 0.f}, sc1[4] = {0.f, 0.f, 0.f, 0.f};
                mma16816(sc, a[0], 0, a[1], 0, b[0], b[1]);
                mma16816(sc1, a[2], 0, a[3], 0, b[2], b[3]);
                bar_arrive(NB_QK2, 384);
                mma16816(sc, a[4], 0, a[5], 0, b[4], b[5]);
                mma16816(sc1, a[6], 0, a[7], 0, b[6], b[7]);
                const float s0 = sc[0] + sc1[0], s1 = sc[1] + sc1[1];
                const uint32_t dst = sb + OFF_S + (vrank() * 5 + j) * 256 + lane * 8;
#pragma unroll
                { const uint32_t q0 = vq0(); for (uint32_t r = 0; r < 3; r++) st_async_v2f(mapa(dst, q0 + r), s0, s1, mapa(bars + BAR_S, q0 + r)); }
            }
            if (s > 0) recycle_slots(s);
            if ((vtid() & 127) == 0) {
                asm volatile("cp.async.bulk.wait_group 0;" ::: "memory");
                store_tile_tma(sb + OFF_Q, &tmQo, (vcta() * 64), s);
                store_tile_tma(sb + OFF_K + 1024, &tmKo, (vcta() * 64), s);
                store_tile_tma(sb + OFF_V + 1024, &tmVo, (vcta() * 64), s);
                bulk_commit();
            }
            {
                float acc[4];
                if (s == 0) mbar_wait(bars + BAR_W3, 0);
                wo_tile_mixed3(acc, WO, sb + OFF_WO + WO_A, sb + OFF_O, bars + BAR_OL, bars + BAR_O, s & 1);
                store_partial(acc, pdA, bars + BAR_R1);
            }
            if ((vtid() & 127) == 0) asm volatile("cp.async.bulk.wait_group.read 0;" ::: "memory");
            bar_sync(NB_WO, 384);
            {
                float d[16];
                mbar_wait(bars + BAR_X, (s + 1) & 1);
                x_part_ss(d, sb + OFF_WV, sb + OFF_X);
                store_xT(sb + OFF_V + 1024, d);
                x_part_rs(d, W, sb + OFF_X);
                store_xT(sb + OFF_Q, d);
                fence_proxy_async();
                if (s + 1 < NSEG - 1) bar_arrive(NB_V, 384);
            }
        }
        bar_arrive(NB_QK2, 384);
        bar_sync(NB_KX, 256);
        bar_sync(NB_WG0, 128);
        if ((vtid() & 127) == 0) {
            asm volatile("cp.async.bulk.wait_group 0;" ::: "memory");
            store_tile_tma(sb + OFF_Q, &tmQo, c0, NSEG - 1);
            store_tile_tma(sb + OFF_K + 1024, &tmKo, c0, NSEG - 1);
            store_tile_tma(sb + OFF_V + 1024, &tmVo, c0, NSEG - 1);
            bulk_commit();
            fence_gpu();
            atomicAdd(&g_cflag[(NSEG - 2) * 8 + (vhead() >> 2)], 1u);
        }
        bar_sync(NB_OUT, 384);
        recycle_slots(NSEG - 1);
        bar_sync(NB_WG0, 128);
        if ((vtid() & 127) == 0) {
            asm volatile("cp.async.bulk.wait_group 0;" ::: "memory");
            fence_gpu();
            atomicAdd(&g_cflag[(NSEG - 1) * 8 + (vhead() >> 2)], 1u);
        }
    } else if (wg == 1) {
        reg_inc<216>();
        uint32_t W[40][4], WO[3][4];
        mbar_wait(bars + BAR_W1, 0);
        load_afrags<40>(W, sb + OFF_WO, (tid >> 5) & 3, tid & 31);
        load_afrags<3>(WO, sb + OFF_X + 12288, (tid >> 5) & 3, tid & 31);
        bar_sync(NB_MEM, 384);
        asm volatile("barrier.cluster.arrive.release.aligned; barrier.cluster.wait.acquire.aligned;" ::: "memory");
        {
            float d[16];
            mbar_wait(bars + BAR_X, 0);
            x_part_rs(d, W, sb + OFF_X);
            store_xT(sb + OFF_K + 1024, d);
            fence_proxy_async();
            bar_arrive(NB_KX, 256);
        }
        const PartialDst pdB = partial_dst(sb, 8);
#pragma unroll 1
        for (int s = 0; s < NSEG; s++) {
            {
                float acc[4];
                mem_part_regs(acc, W, sb + OFF_MEM, bars + BAR_C, s & 1);
                store_memT(sb + OFF_K, acc);
            }
            if (s == NSEG - 1) {
                bar_arrive(NB_QK2, 384);
                bar_sync(NB_WG1, 128);
                copy_rows_out<8>(sb + OFF_K, g_Km + (size_t)s * NMEM * HD + (vcta() * 64));
                bar_arrive(NB_OUT, 384);
                break;
            }
            bar_sync(NB_QK, 256);
            if (((vtid() >> 5) & 3) == 0) {
                const int lane = vtid() & 31;
                const int mid = lane >> 3, i = lane & 7;
                const uint32_t o0 = i * 128 + ((mid ^ i) << 4), o1 = o0 ^ 64;
                uint32_t a[8], b[8];
                ldsm_x4(b[0], b[1], b[2], b[3], sb + OFF_K + o0);
                ldsm_x4(b[4], b[5], b[6], b[7], sb + OFF_K + o1);
                ldsm_x4(a[0], a[1], a[2], a[3], sb + OFF_QM + o0);
                ldsm_x4(a[4], a[5], a[6], a[7], sb + OFF_QM + o1);
                float sc[4] = {0.f, 0.f, 0.f, 0.f}, sc1[4] = {0.f, 0.f, 0.f, 0.f};
                mma16816(sc, a[0], 0, a[1], 0, b[0], b[1]);
                mma16816(sc1, a[2], 0, a[3], 0, b[2], b[3]);
                bar_arrive(NB_QK2, 384);
                mma16816(sc, a[4], 0, a[5], 0, b[4], b[5]);
                mma16816(sc1, a[6], 0, a[7], 0, b[6], b[7]);
                const float s0 = sc[0] + sc1[0], s1 = sc[1] + sc1[1];
                const uint32_t dst = sb + OFF_S + (vrank() * 5) * 256 + lane * 8;
#pragma unroll
                { const uint32_t q0 = vq0(); for (uint32_t r = 0; r < 3; r++) st_async_v2f(mapa(dst, q0 + r), s0, s1, mapa(bars + BAR_S, q0 + r)); }
            } else {
                bar_arrive(NB_QK2, 384);
            }
            {
                const int tt = vtid(), lane = tt & 31, warp = (tt >> 5) & 3;
                mbar_wait(bars + BAR_S, s & 1);
                float sv[10];
#pragma unroll
                for (int j = 0; j < 5; j++) {
                    const float2 p0 = lds64f(sb + OFF_S + (0 * 5 + j) * 256 + lane * 8);
                    const float2 p1 = lds64f(sb + OFF_S + (1 * 5 + j) * 256 + lane * 8);
                    const float2 p2 = lds64f(sb + OFF_S + (2 * 5 + j) * 256 + lane * 8);
                    sv[2 * j] = p0.x + p1.x + p2.x;
                    sv[2 * j + 1] = p0.y + p1.y + p2.y;
                }
                float mx = fmaxf(fmaxf(fmaxf(sv[0], sv[1]), fmaxf(sv[2], sv[3])),
                                 fmaxf(fmaxf(fmaxf(sv[4], sv[5]), fmaxf(sv[6], sv[7])), fmaxf(sv[8], sv[9])));
                mx = fmaxf(mx, __shfl_xor_sync(0xffffffffu, mx, 1));
                mx = fmaxf(mx, __shfl_xor_sync(0xffffffffu, mx, 2));
                const float sl2 = 0.07216878364870322f * 1.4426950408889634f;
#pragma unroll
                for (int j = 0; j < 10; j++) sv[j] = ex2((sv[j] - mx) * sl2);
                uint32_t p[5];
#pragma unroll
                for (int j = 0; j < 5; j++) p[j] = pack_bf16(sv[2 * j], sv[2 * j + 1]);
                float rs[4] = {0.f, 0.f, 0.f, 0.f};
                mma16816(rs, p[0], 0, p[1], 0, 0x3F803F80u, 0x3F803F80u);
                mma16816(rs, p[2], 0, p[3], 0, 0x3F803F80u, 0x3F803F80u);
                mma16816(rs, p[4], 0, 0, 0, 0x3F803F80u, 0);
                bar_sync(NB_V, 384);
                float o0[4] = {0.f, 0.f, 0.f, 0.f}, o1[4] = {0.f, 0.f, 0.f, 0.f};
                const int mid = lane >> 3, i = lane & 7;
                const uint32_t vb = sb + OFF_V + ((mid & 1) * 8 + i) * 128 + (((2 * warp + (mid >> 1)) ^ i) << 4);
                uint32_t b0, b1, b2, b3, b4, b5, b6, b7, b8, b9;
                ldsm_x4_t(b0, b1, b2, b3, vb);
                ldsm_x4_t(b4, b5, b6, b7, vb + 2048);
                ldsm_x2_t(b8, b9, sb + OFF_V + (32 + i) * 128 + (((2 * warp + (mid & 1)) ^ i) << 4));
                mma16816(o0, p[0], 0, p[1], 0, b0, b1);
                mma16816(o1, p[0], 0, p[1], 0, b2, b3);
                mma16816(o0, p[2], 0, p[3], 0, b4, b5);
                mma16816(o1, p[2], 0, p[3], 0, b6, b7);
                mma16816(o0, p[4], 0, 0, 0, b8, 0);
                mma16816(o1, p[4], 0, 0, 0, b9, 0);
                const float inv = rcpf(rs[0]);
                const uint32_t w0 = pack_bf16(o0[0] * inv, o0[1] * inv), w1 = pack_bf16(o1[0] * inv, o1[1] * inv);
                const uint32_t rk = vrank();
                const uint32_t oc = sb + OFF_O + rk * 1024;
                asm volatile("stmatrix.sync.aligned.m8n8.x2.shared.b16 [%0], {%1,%2};"
                             ::"r"(oc + i * 128 + (((2 * warp + (mid & 1)) ^ i) << 4)), "r"(w0), "r"(w1) : "memory");
                fence_proxy_async();
                bar_sync(NB_WG1, 128);
                if (lane == 0) {
                    if (warp == 0) bulk_to_peer(oc, 1024, bars + BAR_O, vq0() + (rk == 0 ? 1 : 0));
                    else if (warp == 1) bulk_to_peer(oc, 1024, bars + BAR_O, vq0() + (rk == 2 ? 1 : 2));
                    else if (warp == 2) mbar_arrive(bars + BAR_OL);
                }
            }
            {
                float acc[4];
                if (s == 0) mbar_wait(bars + BAR_W3, 0);
                wo_tile_mixed3(acc, WO, sb + OFF_WO + WO_B, sb + OFF_O, bars + BAR_OL, bars + BAR_O, s & 1);
                store_partial(acc, pdB, bars + BAR_R1);
            }
            bar_sync(NB_WO, 384);
            copy_rows_out<8>(sb + OFF_K, g_Km + (size_t)s * NMEM * HD + (vcta() * 64));
            {
                float d[16];
                mbar_wait(bars + BAR_X, (s + 1) & 1);
                x_part_rs(d, W, sb + OFF_X);
                store_xT(sb + OFF_K + 1024, d);
                fence_proxy_async();
                bar_arrive(NB_KX, 256);
            }
            if ((vtid() & 127) == 96) {
                fence_gpu();
                if (s > 0) atomicAdd(&g_cflag[(s - 1) * 8 + (vhead() >> 2)], 1u);
            }
            __syncwarp();

        }
    } else {
        reg_dec<64>();
        bar_sync(NB_MEM, 384);
        asm volatile("barrier.cluster.arrive.release.aligned; barrier.cluster.wait.acquire.aligned;" ::: "memory");
        issue_x_load(sb, &tmX, 0);
        if ((tid & 127) == 96) {
            mbar_expect_tx(bars + BAR_W2, 81920);
            for (int i = 0; i < 5; i++) tma_load_2d(sb + OFF_WV + i * 16384, &tmWv, c0, i * 128, bars + BAR_W2);
            mbar_expect_tx(bars + BAR_W3, 18432 + 18432 + 24576 + 8192);
            tma_load_2d(sb + OFF_WO + WO_A, &tmWo, (tb + 0) * 64, h * DH + 48, bars + BAR_W3);
            for (int i = 0; i < 3; i++)
                tma_load_2d(sb + OFF_WO + WO_A + 12288 + i * 2048, &tmWo16, (tb + 0) * 64, h * DH + 144 + 16 * i, bars + BAR_W3);
            tma_load_2d(sb + OFF_WO + WO_B, &tmWo, (tb + 1) * 64, h * DH + 48, bars + BAR_W3);
            for (int i = 0; i < 3; i++)
                tma_load_2d(sb + OFF_WO + WO_B + 12288 + i * 2048, &tmWo16, (tb + 1) * 64, h * DH + 144 + 16 * i, bars + BAR_W3);
            tma_load_2d(sb + OFF_WO + WO_C, &tmWo, (tb + 2) * 64, h * DH, bars + BAR_W3);
            tma_load_2d(sb + OFF_WO + WO_C + 12288, &tmWo, (tb + 2) * 64, h * DH + 96, bars + BAR_W3);
            for (int i = 0; i < 4; i++)
                tma_load_2d(sb + OFF_WO + WO_E + i * 2048, &tmWo16, 576, c0 + 16 * i, bars + BAR_W3);
        }
        {
            const int t = tid & 127;
#pragma unroll
            for (int i = 0; i < 5; i++) {
                const int v = i * 128 + t, cg = v >> 3, tok = v & 7;
                const uint4 val = *reinterpret_cast<const uint4*>(mem0 + tok * DM + cg * 8);
                sts128(sb + OFF_MEM + cg * 128 + tok * 16, val);
            }
        }
        fence_proxy_async();
        mbar_wait(bars + BAR_W2, 0);
        if ((tid & 127) == 0) atomicAdd(&g_wflag, 1u);
        bar_sync(NB_WG2, 128);
        if ((tid & 127) == 0) mbar_arrive(bars + BAR_C);
        const PartialDst pdE = partial_dst_e(sb), pdC = partial_dst(sb, 16);
#pragma unroll 1
        for (int s = 0; s < NSEG; s++) {
            if (s < NSEG - 1) {
                const int t = vtid() & 127;
                if (t == 0) mbar_expect_tx(bars + BAR_S, 3840);
                if (t == 32) mbar_expect_tx(bars + BAR_O, 2048);
                if (t == 64) {
                    const int nh = vnh(), per = nh == 5 ? 5 : 6, j = (int)(vq() / 3);
                    mbar_expect_tx(bars + BAR_R1, (j * per + per <= 24 ? per : 24 - j * per) * nh * 128);
                }
                if (t == 96 && vq() < 8) mbar_expect_tx(bars + BAR_RE, 3 * vnh() * 128);
            }
            bar_sync(NB_QK2, 384);
            {
                float acc[4] = {0.f, 0.f, 0.f, 0.f};
                wg_fence();
                static_for<0, 40>([&](auto I) {
                    constexpr int ks = decltype(I)::value;
                    wgmma_ss_n8_ta_bns<((ks * 2048) >> 4), ((ks * 256) >> 4)>(acc, desc_lo(sb + OFF_WV), (((sb + OFF_MEM) & 0x3FFFF) >> 4) | (8u << 16));
                });
                wg_commit();
                wg_wait<0>();
                store_memT(sb + OFF_V, acc);
            }
            if (s < NSEG - 1) {
                bar_arrive(NB_V, 384);
                mbar_wait(bars + BAR_S, s & 1);
                issue_x_load(sb, &tmX, s + 1);
            }
            bar_sync(NB_WG2, 128);
            copy_rows_out<8>(sb + OFF_V, g_Vm + (size_t)s * NMEM * HD + vcta() * 64);
            if (s == NSEG - 1) { bar_arrive(NB_OUT, 384); break; }
            const int vr = (int)vrank();
            {
                if (s == 0) mbar_wait(bars + BAR_W3, 0);
                mbar_wait(bars + BAR_OL, s & 1);
                float acc[4] = {0.f, 0.f, 0.f, 0.f};
                wg_fence();
                static_for<0, 4>([&](auto I) {
                    constexpr int ks = decltype(I)::value;
                    wgmma_ss_n8_ta<((ks * 2048) >> 4), ((ks * 32) >> 4)>(acc, desc_lo(sb + OFF_WO + WO_E), desc_lo(sb + OFF_O + vr * 1024));
                });
                wg_commit();
                wg_wait<0>();
                store_partial(acc, pdE, bars + BAR_RE);
            }
            {
                float acc[4];
                wo_tile_ss(acc, sb + OFF_WO + WO_C, sb + OFF_O, bars + BAR_OL, bars + BAR_O, s & 1);
                store_partial(acc, pdC, bars + BAR_R1);
            }
            bar_arrive(NB_WO, 384);
            reduce_cluster(s, sb);
            spin_cycles(DELAY_G);
            gather_memory(s, sb, dbg);
        }
    }
}

}

namespace sd {
constexpr int STAGES = 4;
constexpr int STAGE_BYTES = 49152;
constexpr int OFF_STG = STAGES * STAGE_BYTES;
constexpr int OFF_BAR = OFF_STG + 32768;
constexpr int OFF_TASK = OFF_BAR + 128;
constexpr int SMEM_BYTES = OFF_TASK + 64;
enum { T_GATE = 0, T_H = 2, T_O = 3, T_ATT = 4, T_END = 5, T_OF = 6, T_OX = 7 };
constexpr int NCOARSE = 13;
constexpr int N_TASKS = 16 + 16 * 12 + NCOARSE * (12 + 3) + (16 - NCOARSE) * (40 + 10) + 40;
constexpr int GRID = 132;
constexpr int AT_KX = 12288, AT_KM = 24576, AT_VX = 27648, AT_VM = 39936;
}

DEVINL bool flag_ready(const unsigned* p, unsigned target) { return (int)(ld_acquire(p) - target) >= 0; }

DEVINL int4 decode_task(int t) {
    using namespace sd;
    if (t >= N_TASKS) return make_int4(T_END, 0, 0, 0);
    if (t < 16) return make_int4(T_GATE, t, 0, 0);
    t -= 16;
    if (t < 16 * 12) return make_int4(T_H, t / 12, t % 12, 0);
    t -= 16 * 12;
    if (t < NCOARSE * 3) return make_int4(T_O, t / 3, t % 3, 4);
    t -= NCOARSE * 3;
    if (t < (16 - NCOARSE) * 10) return make_int4(T_OF, NCOARSE + t / 10, t % 5, 8 + (t % 10) / 5);
    t -= (16 - NCOARSE) * 10;
    if (t < NCOARSE * 12) return make_int4(T_O, t / 12, (t % 12) % 3, (t % 12) / 3);
    t -= NCOARSE * 12;
    if (t < (15 - NCOARSE) * 40) return make_int4(T_OF, NCOARSE + t / 40, (t % 40) % 5, (t % 40) / 5);
    t -= (15 - NCOARSE) * 40;
    if (t < 80) return make_int4(T_OX, 15, t % 10, t / 10);
    return make_int4(T_END, 0, 0, 0);
}

DEVINL void tma_load_3d(uint32_t dst, const CUtensorMap* map, int c0, int c1, int c2, uint32_t bar) {
    asm volatile(
        "cp.async.bulk.tensor.3d.shared::cluster.global.mbarrier::complete_tx::bytes [%0], [%1, {%3, %4, %5}], [%2];"
        ::"r"(dst), "l"(map), "r"(bar), "r"(c0), "r"(c1), "r"(c2) : "memory");
}
DEVINL float fast_sigmoid(float x) { return rcpf(1.f + ex2(-1.4426950408889634f * x)); }

DEVINL void attention_warp(uint32_t st, int seg, int head, int half, int lane) {
    const uint32_t sQ = st, sKx = st + sd::AT_KX, sKm = st + sd::AT_KM, sVx = st + sd::AT_VX, sVm = st + sd::AT_VM;
    const int mid = lane >> 3, i = lane & 7, g = lane >> 2, c = lane & 3;
    float sc[5][4];
#pragma unroll
    for (int j = 0; j < 5; j++) sc[j][0] = sc[j][1] = sc[j][2] = sc[j][3] = 0.f;
#pragma unroll
    for (int ks = 0; ks < 12; ks++) {
        uint32_t a0, a1, a2, a3;
        {
            const int row = half * 16 + (mid & 1) * 8 + i;
            ldsm_x4(a0, a1, a2, a3, sQ + (ks >> 2) * 4096 + row * 128 + ((((ks & 3) * 2 + (mid >> 1)) ^ i) << 4));
        }
        const uint32_t ksl = (((ks & 3) * 2 + (mid & 1)) ^ i) << 4;
        {
            uint32_t b0, b1, b2, b3;
            const uint32_t addr = (mid >> 1) == 0 ? sKm + (ks >> 2) * 1024 + i * 128 + ksl : sKx + (ks >> 2) * 4096 + i * 128 + ksl;
            ldsm_x4(b0, b1, b2, b3, addr);
            mma16816(sc[0], a0, a1, a2, a3, b0, b1);
            mma16816(sc[1], a0, a1, a2, a3, b2, b3);
        }
        {
            uint32_t b0, b1, b2, b3;
            ldsm_x4(b0, b1, b2, b3, sKx + (ks >> 2) * 4096 + ((1 + (mid >> 1)) * 8 + i) * 128 + ksl);
            mma16816(sc[2], a0, a1, a2, a3, b0, b1);
            mma16816(sc[3], a0, a1, a2, a3, b2, b3);
        }
        {
            uint32_t b0, b1, b2, b3;
            ldsm_x4(b0, b1, b2, b3, sKx + (ks >> 2) * 4096 + (24 + i) * 128 + ksl);
            mma16816(sc[4], a0, a1, a2, a3, b0, b1);
        }
    }
    const float scale = 0.07216878364870322f;
    const int t0 = half * 16 + g, t1 = t0 + 8;
    float m0 = -3.0e38f, m1 = -3.0e38f;
#pragma unroll
    for (int j = 0; j < 5; j++) {
#pragma unroll
        for (int e = 0; e < 2; e++) {
            const int key = 8 * j + 2 * c + e;
            sc[j][e] = (key - 8 <= t0) ? sc[j][e] * scale : -1.0e9f;
            sc[j][2 + e] = (key - 8 <= t1) ? sc[j][2 + e] * scale : -1.0e9f;
            m0 = fmaxf(m0, sc[j][e]);
            m1 = fmaxf(m1, sc[j][2 + e]);
        }
    }
    m0 = fmaxf(m0, __shfl_xor_sync(0xffffffffu, m0, 1)); m0 = fmaxf(m0, __shfl_xor_sync(0xffffffffu, m0, 2));
    m1 = fmaxf(m1, __shfl_xor_sync(0xffffffffu, m1, 1)); m1 = fmaxf(m1, __shfl_xor_sync(0xffffffffu, m1, 2));
    float s0 = 0.f, s1 = 0.f;
#pragma unroll
    for (int j = 0; j < 5; j++) {
#pragma unroll
        for (int e = 0; e < 2; e++) {
            sc[j][e] = ex2((sc[j][e] - m0) * 1.4426950408889634f);
            sc[j][2 + e] = ex2((sc[j][2 + e] - m1) * 1.4426950408889634f);
            s0 += sc[j][e];
            s1 += sc[j][2 + e];
        }
    }
    s0 += __shfl_xor_sync(0xffffffffu, s0, 1); s0 += __shfl_xor_sync(0xffffffffu, s0, 2);
    s1 += __shfl_xor_sync(0xffffffffu, s1, 1); s1 += __shfl_xor_sync(0xffffffffu, s1, 2);
    const float i0 = rcpf(s0), i1 = rcpf(s1);
    uint32_t p[3][4];
#pragma unroll
    for (int ks = 0; ks < 2; ks++) {
        p[ks][0] = pack_bf16(sc[2 * ks][0] * i0, sc[2 * ks][1] * i0);
        p[ks][1] = pack_bf16(sc[2 * ks][2] * i1, sc[2 * ks][3] * i1);
        p[ks][2] = pack_bf16(sc[2 * ks + 1][0] * i0, sc[2 * ks + 1][1] * i0);
        p[ks][3] = pack_bf16(sc[2 * ks + 1][2] * i1, sc[2 * ks + 1][3] * i1);
    }
    p[2][0] = pack_bf16(sc[4][0] * i0, sc[4][1] * i0);
    p[2][1] = pack_bf16(sc[4][2] * i1, sc[4][3] * i1);
    const int row0 = seg * SEG + t0;
    const float g0 = __ldcg(g_gate + row0), g1 = __ldcg(g_gate + row0 + 8);
    bf16* o0 = g_Acat + (size_t)row0 * KCAT + head * DH + 2 * c;
    bf16* o1 = o0 + 8 * KCAT;
#pragma unroll
    for (int np = 0; np < 12; np++) {
        float o[2][4] = {{0.f, 0.f, 0.f, 0.f}, {0.f, 0.f, 0.f, 0.f}};
        const uint32_t vsl = (((np & 3) * 2 + (mid >> 1)) ^ i) << 4;
        {
            uint32_t b0, b1, b2, b3;
            const uint32_t addr = (mid & 1) == 0 ? sVm + (np >> 2) * 1024 + i * 128 + vsl : sVx + (np >> 2) * 4096 + i * 128 + vsl;
            ldsm_x4_t(b0, b1, b2, b3, addr);
            mma16816(o[0], p[0][0], p[0][1], p[0][2], p[0][3], b0, b1);
            mma16816(o[1], p[0][0], p[0][1], p[0][2], p[0][3], b2, b3);
        }
        {
            uint32_t b0, b1, b2, b3;
            ldsm_x4_t(b0, b1, b2, b3, sVx + (np >> 2) * 4096 + (8 + (mid & 1) * 8 + i) * 128 + vsl);
            mma16816(o[0], p[1][0], p[1][1], p[1][2], p[1][3], b0, b1);
            mma16816(o[1], p[1][0], p[1][1], p[1][2], p[1][3], b2, b3);
        }
        {
            uint32_t b0, b2;
            ldsm_x2_t(b0, b2, sVx + (np >> 2) * 4096 + (24 + i) * 128 + ((((np & 3) * 2 + (mid & 1)) ^ i) << 4));
            mma16816(o[0], p[2][0], p[2][1], 0, 0, b0, 0);
            mma16816(o[1], p[2][0], p[2][1], 0, 0, b2, 0);
        }
        const uint32_t r00 = pack_bf16(o[0][0] * g0, o[0][1] * g0), r01 = pack_bf16(o[1][0] * g0, o[1][1] * g0);
        const uint32_t r10 = pack_bf16(o[0][2] * g1, o[0][3] * g1), r11 = pack_bf16(o[1][2] * g1, o[1][3] * g1);
        const bool odd = c & 1;
        const uint32_t x0 = __shfl_xor_sync(0xffffffffu, odd ? r00 : r01, 1);
        const uint32_t x1 = __shfl_xor_sync(0xffffffffu, odd ? r10 : r11, 1);
        const int off = np * 16 + (odd ? 8 - 2 : 0);
        *reinterpret_cast<uint2*>(o0 + off) = odd ? make_uint2(x0, r01) : make_uint2(r00, x0);
        *reinterpret_cast<uint2*>(o1 + off) = odd ? make_uint2(x1, r11) : make_uint2(r10, x1);
    }
}

__global__ void __launch_bounds__(384, 1)
side_kernel(const __grid_constant__ CUtensorMap tmX, const __grid_constant__ CUtensorMap tmWg,
            const __grid_constant__ CUtensorMap tmWu, const __grid_constant__ CUtensorMap tmAcat,
            const __grid_constant__ CUtensorMap tmWo, const __grid_constant__ CUtensorMap tmWd,
            const __grid_constant__ CUtensorMap tmQ, const __grid_constant__ CUtensorMap tmKx,
            const __grid_constant__ CUtensorMap tmVx, const __grid_constant__ CUtensorMap tmKm,
            const __grid_constant__ CUtensorMap tmVm, const bf16* __restrict__ x, const bf16* __restrict__ gw,
            bf16* __restrict__ out, int big_cluster) {
    using namespace sd;
    extern __shared__ __align__(1024) uint8_t smem_raw[];
    const uint32_t sb = smem_u32(smem_raw);
    const uint32_t bars = sb + OFF_BAR;
    volatile int4* tinfo = reinterpret_cast<volatile int4*>(smem_raw + OFF_TASK);
    const int tid = threadIdx.x, wg = tid >> 7;
    const unsigned epoch = *(volatile unsigned*)&g_epoch;
    if (tid == 0) {
        for (int i = 0; i < STAGES; i++) { mbar_init(bars + i * 8, 1); mbar_init(bars + 32 + i * 8, 2); }
        for (int i = 0; i < 2; i++) { mbar_init(bars + 64 + i * 8, 1); mbar_init(bars + 80 + i * 8, 2); }
        asm volatile("fence.mbarrier_init.release.cluster;" ::: "memory");
    }
    __syncthreads();
    if (wg == 0) {
        reg_dec<40>();
        if (tid == 0) {
            uint32_t it = 0;
            const unsigned tbase = epoch * (unsigned)(N_TASKS + GRID);
            int4 held = make_int4(-1, 0, 0, 0);
            int held_ticket = 0, gate_seen = -1;
            int curseg = (int)*(volatile unsigned*)&g_segcnt[NSEG];
            for (uint32_t nt = 0;; nt++) {
                int4 task;
                int ticket;
                uint32_t spins = 0;
                while (true) {
                    if (curseg < NSEG && flag_ready(&g_cflag[curseg * 8], (epoch + 1) * 12) &&
                        (gate_seen == (curseg >> 2) || flag_ready(&g_gflag[curseg >> 2], epoch + 1))) {
                        gate_seen = curseg >> 2;
                        const unsigned hg = atomicAdd(&g_segcnt[curseg], 1u);
                        if (hg < 8) {
                            if (hg) wait_flag(&g_cflag[curseg * 8 + hg], (epoch + 1) * 12);
                            task = make_int4(T_ATT, curseg, (int)hg, 0);
                            ticket = N_TASKS + curseg * 8 + (int)hg;
                            break;
                        }
                        curseg++;
                        atomicMax(&g_segcnt[NSEG], (unsigned)curseg);
                        continue;
                    }
                    if (held.x < 0) {
                        held_ticket = (int)(atomicAdd(&g_ticket, 1u) - tbase);
                        held = decode_task(held_ticket);
                    }
                    bool ready = true;
                    if (held.x == T_O) {
                        if (held.w < 4) ready = flag_ready(&g_aflag[held.y * 8 + 2 * held.w], (epoch + 1) * 4) && flag_ready(&g_aflag[held.y * 8 + 2 * held.w + 1], (epoch + 1) * 4);
                        else ready = flag_ready(&g_hflag[held.y * 2], (epoch + 1) * 6) && flag_ready(&g_hflag[held.y * 2 + 1], (epoch + 1) * 6);
                    } else if (held.x == T_OX) {
                        ready = flag_ready(&g_aflag[held.y * 8 + held.w], (epoch + 1) * 4);
                    } else if (held.x == T_OF) {
                        ready = held.w < 8 ? flag_ready(&g_aflag[held.y * 8 + held.w], (epoch + 1) * 4) : flag_ready(&g_hflag[held.y * 2 + held.w - 8], (epoch + 1) * 6);
                    } else if (held.x == T_H && held.y < 4) {
                        ready = flag_ready(&g_wflag, (epoch + 1) * 96);
                    } else if (held.x == T_END) {
                        ready = curseg >= NSEG;
                    }
                    if (ready || ++spins > (1u << 24)) {
                        task = held; ticket = held_ticket;
                        if (held.x != T_END) held.x = -1;
                        break;
                    }
                    __nanosleep(64);
                }
                asm volatile("fence.proxy.async;" ::: "memory");
                const int sl = nt & 1;
                mbar_wait(bars + 80 + sl * 8, ((nt >> 1) & 1) ^ 1);
                tinfo[sl].x = task.x | (ticket << 4); tinfo[sl].y = task.y; tinfo[sl].z = task.z; tinfo[sl].w = task.w;
                mbar_arrive(bars + 64 + sl * 8);
                if (task.x == T_END) break;
                if (task.x == T_GATE) continue;
                if (task.x == T_ATT) {
                    for (int j = 0; j < 4; j++, it++) {
                        const int st = it % STAGES;
                        mbar_wait(bars + 32 + st * 8, ((it / STAGES) & 1) ^ 1);
                        const uint32_t sS = sb + st * STAGE_BYTES, fb = bars + st * 8;
                        const int head = task.z * 4 + j, seg = task.y;
                        mbar_expect_tx(fb, 43008);
                        tma_load_3d(sS, &tmQ, 0, seg * SEG, head * 3, fb);
                        tma_load_3d(sS + AT_KX, &tmKx, 0, seg * SEG, head * 3, fb);
                        tma_load_3d(sS + AT_KM, &tmKm, 0, seg * NMEM, head * 3, fb);
                        tma_load_3d(sS + AT_VX, &tmVx, 0, seg * SEG, head * 3, fb);
                        tma_load_3d(sS + AT_VM, &tmVm, 0, seg * NMEM, head * 3, fb);
                    }
                    continue;
                }
                int nkb, kb0, n0, nw;
                if (task.x == T_H) { nkb = 10; kb0 = 0; n0 = task.z * 128; nw = 256; }
                else if (task.x == T_O) { nkb = 24; kb0 = task.w * 24; n0 = task.z * 256; nw = task.z < 2 ? 256 : 128; }
                else if (task.x == T_OF) { nkb = 12; kb0 = task.w * 12; n0 = task.z * 128; nw = 128; }
                else { nkb = 12; kb0 = task.w * 12; n0 = task.z * 64; nw = 64; }
                for (int kb = 0; kb < nkb; kb++) {
                    const int st = it % STAGES;
                    mbar_wait(bars + 32 + st * 8, ((it / STAGES) & 1) ^ 1);
                    const uint32_t sA = sb + st * STAGE_BYTES, sB = sA + 16384, fb = bars + st * 8;
                    if (task.x == T_H) {
                        mbar_expect_tx(fb, 49152);
                        tma_load_2d(sA, &tmX, kb * 64, task.y * 128, fb);
                        tma_load_2d(sB, &tmWg, n0, kb * 64, fb);
                        tma_load_2d(sB + 8192, &tmWg, n0 + 64, kb * 64, fb);
                        tma_load_2d(sB + 16384, &tmWu, n0, kb * 64, fb);
                        tma_load_2d(sB + 24576, &tmWu, n0 + 64, kb * 64, fb);
                    } else {
                        mbar_expect_tx(fb, 16384 + nw * 128);
                        const int k0 = (kb0 + kb) * 64;
                        tma_load_2d(sA, &tmAcat, k0, task.y * 128, fb);
                        const CUtensorMap* m = k0 < HD ? &tmWo : &tmWd;
                        const int krow = k0 < HD ? k0 : k0 - HD;
                        for (int j = 0; j < nw / 64; j++) tma_load_2d(sB + j * 8192, m, n0 + j * 64, krow, fb);
                    }
                    it++;
                }
            }
            __threadfence();
            const unsigned e = atomicAdd(&g_exit, 1u);
            if (e == epoch * GRID + GRID - 1) {
                for (int i = 0; i <= NSEG; i++) g_segcnt[i] = 0;
                __threadfence();
                atomicAdd(&g_epoch, 1u);
            }
        }
    } else {
        reg_inc<232>();
        const int ct = tid - 128, cw = wg - 1, warp = (tid >> 5) & 3, lane = tid & 31;
        uint32_t it = 0;
        for (uint32_t nt = 0;; nt++) {
            const int sl = nt & 1;
            mbar_wait(bars + 64 + sl * 8, (nt >> 1) & 1);
            const int tword = tinfo[sl].x, ttype = tword & 15, ty = tinfo[sl].y, tz = tinfo[sl].z, tw = tinfo[sl].w;
            bar_sync(2 + cw, 128);
            if ((tid & 127) == 0) mbar_arrive(bars + 80 + sl * 8);
            if (ttype == T_END) break;
            if (ttype == T_GATE) {
                const __nv_bfloat162* wr = reinterpret_cast<const __nv_bfloat162*>(gw);
                float2 wv[10];
#pragma unroll
                for (int i = 0; i < 10; i++) wv[i] = __bfloat1622float2(wr[i * 32 + lane]);
#pragma unroll 1
                for (int r = 0; r < 16; r += 8) {
                    __nv_bfloat162 xv[8][10];
#pragma unroll
                    for (int q = 0; q < 8; q++) {
                        const __nv_bfloat162* xr = reinterpret_cast<const __nv_bfloat162*>(x + (size_t)(ty * 128 + (ct >> 5) * 16 + r + q) * DM);
#pragma unroll
                        for (int i = 0; i < 10; i++) xv[q][i] = xr[i * 32 + lane];
                    }
#pragma unroll
                    for (int q = 0; q < 8; q++) {
                        float acc = 0.f;
#pragma unroll
                        for (int i = 0; i < 10; i++) {
                            const float2 a = __bfloat1622float2(xv[q][i]);
                            acc += a.x * wv[i].x + a.y * wv[i].y;
                        }
#pragma unroll
                        for (int o = 16; o; o >>= 1) acc += __shfl_xor_sync(0xffffffffu, acc, o);
                        if (lane == 0) g_gate[ty * 128 + (ct >> 5) * 16 + r + q] = 1.f / (1.f + __expf(-acc));
                    }
                }
                bar_sync(1, 256);
                if (ct == 0) signal_flag(&g_gflag[ty]);
                continue;
            }
            if (ttype == T_ATT) {
                const int j = ct >> 6, st = (it + j) % STAGES;
                mbar_wait(bars + st * 8, ((it + j) / STAGES) & 1);
                attention_warp(sb + st * STAGE_BYTES, ty, tz * 4 + j, (ct >> 5) & 1, lane);
                bar_sync(1, 256);
                if ((tid & 127) == 0)
                    for (int q = 0; q < STAGES; q++) mbar_arrive(bars + 32 + ((it + q) % STAGES) * 8);
                it += STAGES;
                if (ct == 0) signal_flag(&g_aflag[(ty >> 2) * 8 + tz]);
                continue;
            }
            float acc[128];
#pragma unroll
            for (int i = 0; i < 128; i++) acc[i] = 0.f;
            const bool wide = ttype == T_H || (ttype == T_O && tz < 2);
            const int nkb = ttype == T_H ? 10 : (ttype == T_O ? 24 : 12);
            for (int kb = 0; kb < nkb; kb++, it++) {
                const int st = it % STAGES;
                mbar_wait(bars + st * 8, (it / STAGES) & 1);
                const uint32_t sA = sb + st * STAGE_BYTES + cw * 8192, sB = sb + st * STAGE_BYTES + 16384;
                const uint32_t alo = desc_lo(sA), blo = ((sB & 0x3FFFF) >> 4) | (512u << 16);
                wg_fence();
                if (wide) {
#pragma unroll
                    for (int ks = 0; ks < 4; ks++) wgmma_ss_n256_tb(acc, alo + ks * 2, blo + ks * 128);
                } else if (ttype == T_OX) {
#pragma unroll
                    for (int ks = 0; ks < 4; ks++) wgmma_ss_n64_tb(acc, alo + ks * 2, blo + ks * 128);
                } else {
#pragma unroll
                    for (int ks = 0; ks < 4; ks++) wgmma_ss_n128_tb(acc, alo + ks * 2, blo + ks * 128);
                }
                wg_commit();
                if (kb > 0) {
                    wg_wait<1>();
                    if ((tid & 127) == 0) mbar_arrive(bars + 32 + ((it - 1) % STAGES) * 8);
                }
            }
            wg_wait<0>();
            if ((tid & 127) == 0) mbar_arrive(bars + 32 + ((it - 1) % STAGES) * 8);
            const int g = lane >> 2, c = lane & 3;
            const int row0 = ty * 128 + cw * 64 + warp * 16 + g;
            if (ttype == T_H) {
                if (ct == 0) wait_flag(&g_gflag[ty], epoch + 1);
                bar_sync(1, 256);
                const float s0 = 1.f - __ldcg(g_gate + row0), s1 = 1.f - __ldcg(g_gate + row0 + 8);
                const uint32_t stg = sb + OFF_STG + cw * 16384;
                const int i8 = lane & 7, mid = lane >> 3;
                const int srow = warp * 16 + (mid & 1) * 8 + i8;
#pragma unroll
                for (int jj = 0; jj < 8; jj++) {
                    uint32_t r[4];
#pragma unroll
                    for (int q = 0; q < 2; q++) {
                        const int j = 2 * jj + q;
                        r[2 * q] = pack_bf16(acc[64 + 4 * j + 0] * fast_sigmoid(acc[4 * j + 0]) * s0, acc[64 + 4 * j + 1] * fast_sigmoid(acc[4 * j + 1]) * s0);
                        r[2 * q + 1] = pack_bf16(acc[64 + 4 * j + 2] * fast_sigmoid(acc[4 * j + 2]) * s1, acc[64 + 4 * j + 3] * fast_sigmoid(acc[4 * j + 3]) * s1);
                    }
                    const int chunk = 2 * jj + (mid >> 1);
                    stsm_x4(stg + srow * 256 + ((chunk ^ (srow & 7)) << 4), r[0], r[1], r[2], r[3]);
                }
                bar_sync(2 + cw, 128);
                bf16* dst = g_Acat + (size_t)(ty * 128 + cw * 64) * KCAT + HD + tz * 128;
#pragma unroll
                for (int q = 0; q < 8; q++) {
                    const int v = q * 128 + (tid & 127), r = v >> 4, ch = v & 15;
                    stg128(dst + (size_t)r * KCAT + ch * 8, lds128(stg + r * 256 + ((ch ^ (r & 7)) << 4)));
                }
                bar_sync(1, 256);
                if (ct == 0) signal_flag(&g_hflag[ty * 2 + tz / 6]);
            } else {
                const int n0 = ttype == T_O ? tz * 256 : (ttype == T_OF ? tz * 128 : tz * 64);
                float* a0 = g_acc + (size_t)row0 * DM + n0 + 2 * c;
                float* a1 = a0 + 8 * DM;
#pragma unroll
                for (int j = 0; j < 8; j++) {
                    asm volatile("red.relaxed.gpu.global.add.v2.f32 [%0], {%1,%2};" ::"l"(a0 + 8 * j), "f"(acc[4 * j + 0]), "f"(acc[4 * j + 1]) : "memory");
                    asm volatile("red.relaxed.gpu.global.add.v2.f32 [%0], {%1,%2};" ::"l"(a1 + 8 * j), "f"(acc[4 * j + 2]), "f"(acc[4 * j + 3]) : "memory");
                }
                if (ttype != T_OX) {
#pragma unroll
                    for (int j = 8; j < 16; j++) {
                        asm volatile("red.relaxed.gpu.global.add.v2.f32 [%0], {%1,%2};" ::"l"(a0 + 8 * j), "f"(acc[4 * j + 0]), "f"(acc[4 * j + 1]) : "memory");
                        asm volatile("red.relaxed.gpu.global.add.v2.f32 [%0], {%1,%2};" ::"l"(a1 + 8 * j), "f"(acc[4 * j + 2]), "f"(acc[4 * j + 3]) : "memory");
                    }
                }
                if (wide) {
#pragma unroll
                    for (int j = 16; j < 32; j++) {
                        asm volatile("red.relaxed.gpu.global.add.v2.f32 [%0], {%1,%2};" ::"l"(a0 + 8 * j), "f"(acc[4 * j + 0]), "f"(acc[4 * j + 1]) : "memory");
                        asm volatile("red.relaxed.gpu.global.add.v2.f32 [%0], {%1,%2};" ::"l"(a1 + 8 * j), "f"(acc[4 * j + 2]), "f"(acc[4 * j + 3]) : "memory");
                    }
                }
                bar_sync(1, 256);
                volatile int* lastp = reinterpret_cast<volatile int*>(smem_raw + OFF_TASK + 32);
                if (ct == 0) {
                    fence_gpu();
                    const unsigned target = (epoch + 1) * (ty < NCOARSE ? 5u : (ty < 15 ? 10u : 18u));
                    int last = 0;
                    const int t5 = n0 >> 7;
                    if (atomicAdd(&g_oflag[ty * 5 + t5], 1u) == target - 1) last |= 1;
                    if (wide && atomicAdd(&g_oflag[ty * 5 + t5 + 1], 1u) == target - 1) last |= 2;
                    if (last) fence_gpu();
                    *lastp = last;
                }
                bar_sync(1, 256);
                const int last = *lastp;
                for (int hsel = 0; hsel < 2; hsel++) {
                    if (!(last & (1 << hsel))) continue;
                    const int cbase = ((n0 >> 7) + hsel) * 128;
                    if (ty == 15 && cbase == 0) {
                        if (big_cluster) {
                            for (int i = ct * 4; i < 80 * 7 * 32; i += 1024)
                                st_relaxed_v4(g_P2 + ((NSEG - 1) & 3) * 80 * 7 * 32 + i, 0u, 0u, 0u, 0u);
                        } else {
                            for (int i = ct * 4; i < MBREP * 3072; i += 1024)
                                st_relaxed_v4(g_MB + ((NSEG - 1) & 3) * MBREP * 3072 + i, 0u, 0u, 0u, 0u);
                        }
                    }
                    float4 val[16];
#pragma unroll
                    for (int i = 0; i < 16; i++) {
                        const int v = i * 256 + ct, r = v >> 5, c4 = v & 31;
                        val[i] = __ldcg(reinterpret_cast<const float4*>(g_acc + (size_t)(ty * 128 + r) * DM + cbase + c4 * 4));
                    }
#pragma unroll
                    for (int i = 0; i < 16; i++) {
                        const int v = i * 256 + ct, r = v >> 5, c4 = v & 31;
                        __stcg(reinterpret_cast<float4*>(g_acc + (size_t)(ty * 128 + r) * DM + cbase + c4 * 4), make_float4(0.f, 0.f, 0.f, 0.f));
                        uint2 o;
                        o.x = pack_bf16(val[i].x, val[i].y);
                        o.y = pack_bf16(val[i].z, val[i].w);
                        *reinterpret_cast<uint2*>(out + (size_t)(ty * 128 + r) * DM + cbase + c4 * 4) = o;
                    }
                }
                bar_sync(1, 256);
            }
        }
    }
}

typedef CUresult (*PFN_encodeTiled)(CUtensorMap*, CUtensorMapDataType, cuuint32_t, void*, const cuuint64_t*,
                                    const cuuint64_t*, const cuuint32_t*, const cuuint32_t*, CUtensorMapInterleave,
                                    CUtensorMapSwizzle, CUtensorMapL2promotion, CUtensorMapFloatOOBfill);

static PFN_encodeTiled get_encode() {
    static PFN_encodeTiled fn = nullptr;
    if (!fn) {
        void* p = nullptr;
        cudaDriverEntryPointQueryResult q;
        cudaGetDriverEntryPoint("cuTensorMapEncodeTiled", &p, cudaEnableDefault, &q);
        fn = (PFN_encodeTiled)p;
    }
    return fn;
}

static CUtensorMap make_map(const void* ptr, uint64_t rows, uint64_t cols, uint32_t br, uint32_t bc,
                            CUtensorMapSwizzle swz = CU_TENSOR_MAP_SWIZZLE_128B) {
    CUtensorMap m;
    cuuint64_t dims[2] = {cols, rows};
    cuuint64_t strides[1] = {cols * 2};
    cuuint32_t box[2] = {bc, br};
    cuuint32_t es[2] = {1, 1};
    get_encode()(&m, CU_TENSOR_MAP_DATA_TYPE_BFLOAT16, 2, const_cast<void*>(ptr), dims, strides, box, es,
                 CU_TENSOR_MAP_INTERLEAVE_NONE, swz, CU_TENSOR_MAP_L2_PROMOTION_L2_256B,
                 CU_TENSOR_MAP_FLOAT_OOB_FILL_NONE);
    return m;
}

static CUtensorMap make_map3(const void* ptr, uint64_t rows, uint64_t cols, uint32_t br, uint32_t bg) {
    CUtensorMap m;
    cuuint64_t dims[3] = {64, rows, cols / 64};
    cuuint64_t strides[2] = {cols * 2, 128};
    cuuint32_t box[3] = {64, br, bg};
    cuuint32_t es[3] = {1, 1, 1};
    get_encode()(&m, CU_TENSOR_MAP_DATA_TYPE_BFLOAT16, 3, const_cast<void*>(ptr), dims, strides, box, es,
                 CU_TENSOR_MAP_INTERLEAVE_NONE, CU_TENSOR_MAP_SWIZZLE_128B, CU_TENSOR_MAP_L2_PROMOTION_L2_256B,
                 CU_TENSOR_MAP_FLOAT_OOB_FILL_NONE);
    return m;
}

extern "C" void kernel_launch(void* const* d_in, const int* in_sizes, int n_in, void* d_out, int out_size) {
    (void)in_sizes; (void)n_in; (void)out_size;
    const bf16* A_x = (const bf16*)d_in[0];
    const bf16* mem0 = (const bf16*)d_in[1];
    const bf16* gate_w = (const bf16*)d_in[11];
    static bool init = false;
    static CUtensorMap tmWq, tmWk, tmWv, tmWo, tmWo16, tmX, tmX128, tmWg, tmWu, tmWd, tmWo64, tmAcat, tmQ, tmKx, tmVx, tmQ3, tmKx3, tmVx3, tmKm, tmVm;
    static void* cached[12];
    static int use_big = 0;
    bool same = init;
    for (int i = 0; i < 12 && same; i++) same = cached[i] == d_in[i];
    if (!same) {
        for (int i = 0; i < 12; i++) cached[i] = d_in[i];
        tmWq = make_map(d_in[2], DM, HD, 128, 64);
        tmWk = make_map(d_in[3], DM, HD, 128, 64);
        tmWv = make_map(d_in[4], DM, HD, 128, 64);
        tmWo = make_map(d_in[5], HD, DM, 96, 64);
        tmWo16 = make_map(d_in[5], HD, DM, 16, 64);
        tmX = make_map(A_x, SEQ, DM, 32, 64);
        tmX128 = make_map(A_x, SEQ, DM, 128, 64);
        tmWg = make_map(d_in[8], DM, FF, 64, 64);
        tmWu = make_map(d_in[9], DM, FF, 64, 64);
        tmWd = make_map(d_in[10], FF, DM, 64, 64);
        tmWo64 = make_map(d_in[5], HD, DM, 64, 64);
        void* p = nullptr;
        cudaGetSymbolAddress(&p, g_Acat);
        tmAcat = make_map(p, SEQ, KCAT, 128, 64);
        cudaGetSymbolAddress(&p, g_Qx);
        tmQ = make_map(p, SEQ, HD, 32, 64);
        tmQ3 = make_map3(p, SEQ, HD, 32, 3);
        cudaGetSymbolAddress(&p, g_Kx);
        tmKx = make_map(p, SEQ, HD, 32, 64);
        tmKx3 = make_map3(p, SEQ, HD, 32, 3);
        cudaGetSymbolAddress(&p, g_Vx);
        tmVx = make_map(p, SEQ, HD, 32, 64);
        tmVx3 = make_map3(p, SEQ, HD, 32, 3);
        cudaGetSymbolAddress(&p, g_Km);
        tmKm = make_map3(p, NSEG * NMEM, HD, 8, 3);
        cudaGetSymbolAddress(&p, g_Vm);
        tmVm = make_map3(p, NSEG * NMEM, HD, 8, 3);
        cudaFuncSetAttribute(csmall::chain_kernel, cudaFuncAttributeMaxDynamicSharedMemorySize, csmall::ch::SMEM_BYTES);
        cudaFuncSetAttribute(cbig::chain_big_kernel, cudaFuncAttributeMaxDynamicSharedMemorySize, cbig::ch::SMEM_BYTES);
        {
            int nc = 0;
            if (cudaFuncSetAttribute(cbig::chain_big_kernel, cudaFuncAttributeNonPortableClusterSizeAllowed, 1) == cudaSuccess) {
                cudaLaunchConfig_t q = {};
                q.gridDim = dim3(105); q.blockDim = dim3(384); q.dynamicSmemBytes = cbig::ch::SMEM_BYTES;
                cudaLaunchAttribute qa[1];
                qa[0].id = cudaLaunchAttributeClusterDimension;
                qa[0].val.clusterDim.x = 15; qa[0].val.clusterDim.y = 1; qa[0].val.clusterDim.z = 1;
                q.attrs = qa; q.numAttrs = 1;
                if (cudaOccupancyMaxActiveClusters(&nc, cbig::chain_big_kernel, &q) != cudaSuccess) nc = 0;
            }
            (void)cudaGetLastError();
            use_big = nc >= 7;
        }
        cudaFuncSetAttribute(side_kernel, cudaFuncAttributeMaxDynamicSharedMemorySize, sd::SMEM_BYTES);
        init = true;
    }
    cudaStream_t st = cudaStreamPerThread;
    {
        cudaLaunchConfig_t cfg = {};
        cfg.gridDim = dim3(use_big ? 105 : 96); cfg.blockDim = dim3(384); cfg.stream = st;
        cfg.dynamicSmemBytes = use_big ? cbig::ch::SMEM_BYTES : csmall::ch::SMEM_BYTES;
        cudaLaunchAttribute at_[1];
        at_[0].id = cudaLaunchAttributeClusterDimension;
        at_[0].val.clusterDim.x = use_big ? 15 : 3; at_[0].val.clusterDim.y = 1; at_[0].val.clusterDim.z = 1;
        cfg.attrs = at_; cfg.numAttrs = 1;
        cudaLaunchKernelEx(&cfg, use_big ? cbig::chain_big_kernel : csmall::chain_kernel, tmWq, tmWk, tmWv, tmWo, tmWo16, tmX, tmQ, tmKx,
                           tmVx, mem0, (long long*)nullptr);
    }
    {
        cudaLaunchConfig_t cfg = {};
        cfg.gridDim = dim3(sd::GRID); cfg.blockDim = dim3(384); cfg.dynamicSmemBytes = sd::SMEM_BYTES; cfg.stream = st;
        cudaLaunchAttribute at_[1];
        at_[0].id = cudaLaunchAttributeProgrammaticStreamSerialization;
        at_[0].val.programmaticStreamSerializationAllowed = 1;
        cfg.attrs = at_; cfg.numAttrs = 1;
        cudaLaunchKernelEx(&cfg, side_kernel, tmX128, tmWg, tmWu, tmAcat, tmWo64, tmWd, tmQ3, tmKx3, tmVx3, tmKm, tmVm, A_x, gate_w,
                           (bf16*)d_out, use_big);
    }
}
```
